```python
import torch

def _softmax(x, axis=-1):
    return torch.softmax(x, dim=axis)
def _gelu(x):
    return torch.nn.functional.gelu(x, approximate="tanh")
def _silu(x):
    return torch.nn.functional.silu(x)
def _sigmoid(x):
    return torch.sigmoid(x)
def _layernorm(x, axis=-1, eps=1e-5):
    m = x.mean(dim=axis, keepdim=True)
    v = x.var(dim=axis, keepdim=True, unbiased=False)
    return (x - m) / torch.sqrt(v + eps)
def _scatter_add(tgt, idx, src, axis=0):
    return tgt.clone().index_add_(axis, idx, src)
def _segment_sum(src, seg, n):
    out = torch.zeros((n,) + src.shape[1:], dtype=src.dtype)
    return out.index_add_(0, seg, src)
def _pad(x, pw):
    flat = tuple(v for pair in reversed(pw) for v in pair)
    return torch.nn.functional.pad(x, flat)

kernel_name = 'standalone__gqa_block_cached__near_ridge'

def setup_inputs():

    _w = (lambda a: (lambda t: t.to(torch.bfloat16) if t.is_floating_point() else t)(torch.as_tensor(a)))
    B, Sq, D = 32, 160, 640
    Hq, Hkv, Sk, Dh = 32, 32, 512, 128
    assert Hq % Hkv == 0, (Hq, Hkv)
    return {
        "x": _w((lambda *s: torch.randn(*s, dtype=torch.bfloat16) * 0.8)(B, Sq, D)),
        "k_cache": _w((lambda *s: torch.randn(*s, dtype=torch.bfloat16) * 0.8)(B, Hkv, Sk, Dh)),
        "v_cache": _w((lambda *s: torch.randn(*s, dtype=torch.bfloat16) * 0.05)(B, Hkv, Sk, Dh)),
        "wq": _w((lambda *s: torch.randn(*s, dtype=torch.bfloat16) * 0.8)(D, Hq * Dh) * (D ** -0.5)),
        "wo": _w((lambda *s: torch.randn(*s, dtype=torch.bfloat16) * 0.05)(Hq * Dh, D) * ((Hq * Dh) ** -0.5)),
    }

def reference(x, k_cache, v_cache, wq, wo):
    B, Sq, D = x.shape
    Hq, Dh = 32, 128
    Hkv = k_cache.shape[1]
    rep = Hq // Hkv
    q = (lambda x, *d: x.permute(*d))((x @ wq).reshape(B, Sq, Hq, Dh), 0, 2, 1, 3)
    k = (lambda x, n, axis: torch.repeat_interleave(x, n, dim=axis))(k_cache, rep, axis=1)
    v = (lambda x, n, axis: torch.repeat_interleave(x, n, dim=axis))(v_cache, rep, axis=1)
    scores = torch.einsum("bhqd,bhkd->bhqk", q, k) * (Dh ** -0.5)
    p = _softmax(scores, axis=-1)
    o = torch.einsum("bhqk,bhkd->bhqd", p, v)
    return (lambda x, *d: x.permute(*d))(o, 0, 2, 1, 3).reshape(B, Sq, Hq * Dh) @ wo
```

```cpp
#include <cuda_runtime.h>
#include <cuda_bf16.h>
#include <cuda.h>
#include <stdint.h>

template<int N, int TA, int TB> struct WgSS;
template<int N, int TB> struct WgRS;
template<int TA, int TB> struct WgSS<32, TA, TB> {
  static __device__ __forceinline__ void mma(float (&d)[16], uint64_t da, uint64_t db, int sd) {
    asm volatile("{\n.reg .pred p;\nsetp.ne.b32 p, %18, 0;\n"
      "wgmma.mma_async.sync.aligned.m64n32k16.f32.bf16.bf16 {%0, %1, %2, %3, %4, %5, %6, %7, %8, %9, %10, %11, %12, %13, %14, %15}, %16, %17, p, 1, 1, %19, %20;\n}\n"
      : "+f"(d[0]), "+f"(d[1]), "+f"(d[2]), "+f"(d[3]), "+f"(d[4]), "+f"(d[5]), "+f"(d[6]), "+f"(d[7]), "+f"(d[8]), "+f"(d[9]), "+f"(d[10]), "+f"(d[11]), "+f"(d[12]), "+f"(d[13]), "+f"(d[14]), "+f"(d[15])
      : "l"(da), "l"(db), "r"(sd), "n"(TA), "n"(TB));
  }
  static __device__ __forceinline__ void mma0(float (&d)[16], uint64_t da, uint64_t db) {
    asm volatile("{\n.reg .pred p;\nsetp.ne.b32 p, 0, 0;\n"
      "wgmma.mma_async.sync.aligned.m64n32k16.f32.bf16.bf16 {%0, %1, %2, %3, %4, %5, %6, %7, %8, %9, %10, %11, %12, %13, %14, %15}, %16, %17, p, 1, 1, %18, %19;\n}\n"
      : "=f"(d[0]), "=f"(d[1]), "=f"(d[2]), "=f"(d[3]), "=f"(d[4]), "=f"(d[5]), "=f"(d[6]), "=f"(d[7]), "=f"(d[8]), "=f"(d[9]), "=f"(d[10]), "=f"(d[11]), "=f"(d[12]), "=f"(d[13]), "=f"(d[14]), "=f"(d[15])
      : "l"(da), "l"(db), "n"(TA), "n"(TB));
  }
};
template<int TA, int TB> struct WgSS<128, TA, TB> {
  static __device__ __forceinline__ void mma(float (&d)[64], uint64_t da, uint64_t db, int sd) {
    asm volatile("{\n.reg .pred p;\nsetp.ne.b32 p, %66, 0;\n"
      "wgmma.mma_async.sync.aligned.m64n128k16.f32.bf16.bf16 {%0, %1, %2, %3, %4, %5, %6, %7, %8, %9, %10, %11, %12, %13, %14, %15, %16, %17, %18, %19, %20, %21, %22, %23, %24, %25, %26, %27, %28, %29, %30, %31, %32, %33, %34, %35, %36, %37, %38, %39, %40, %41, %42, %43, %44, %45, %46, %47, %48, %49, %50, %51, %52, %53, %54, %55, %56, %57, %58, %59, %60, %61, %62, %63}, %64, %65, p, 1, 1, %67, %68;\n}\n"
      : "+f"(d[0]), "+f"(d[1]), "+f"(d[2]), "+f"(d[3]), "+f"(d[4]), "+f"(d[5]), "+f"(d[6]), "+f"(d[7]), "+f"(d[8]), "+f"(d[9]), "+f"(d[10]), "+f"(d[11]), "+f"(d[12]), "+f"(d[13]), "+f"(d[14]), "+f"(d[15]), "+f"(d[16]), "+f"(d[17]), "+f"(d[18]), "+f"(d[19]), "+f"(d[20]), "+f"(d[21]), "+f"(d[22]), "+f"(d[23]), "+f"(d[24]), "+f"(d[25]), "+f"(d[26]), "+f"(d[27]), "+f"(d[28]), "+f"(d[29]), "+f"(d[30]), "+f"(d[31]), "+f"(d[32]), "+f"(d[33]), "+f"(d[34]), "+f"(d[35]), "+f"(d[36]), "+f"(d[37]), "+f"(d[38]), "+f"(d[39]), "+f"(d[40]), "+f"(d[41]), "+f"(d[42]), "+f"(d[43]), "+f"(d[44]), "+f"(d[45]), "+f"(d[46]), "+f"(d[47]), "+f"(d[48]), "+f"(d[49]), "+f"(d[50]), "+f"(d[51]), "+f"(d[52]), "+f"(d[53]), "+f"(d[54]), "+f"(d[55]), "+f"(d[56]), "+f"(d[57]), "+f"(d[58]), "+f"(d[59]), "+f"(d[60]), "+f"(d[61]), "+f"(d[62]), "+f"(d[63])
      : "l"(da), "l"(db), "r"(sd), "n"(TA), "n"(TB));
  }
  static __device__ __forceinline__ void mma0(float (&d)[64], uint64_t da, uint64_t db) {
    asm volatile("{\n.reg .pred p;\nsetp.ne.b32 p, 0, 0;\n"
      "wgmma.mma_async.sync.aligned.m64n128k16.f32.bf16.bf16 {%0, %1, %2, %3, %4, %5, %6, %7, %8, %9, %10, %11, %12, %13, %14, %15, %16, %17, %18, %19, %20, %21, %22, %23, %24, %25, %26, %27, %28, %29, %30, %31, %32, %33, %34, %35, %36, %37, %38, %39, %40, %41, %42, %43, %44, %45, %46, %47, %48, %49, %50, %51, %52, %53, %54, %55, %56, %57, %58, %59, %60, %61, %62, %63}, %64, %65, p, 1, 1, %66, %67;\n}\n"
      : "=f"(d[0]), "=f"(d[1]), "=f"(d[2]), "=f"(d[3]), "=f"(d[4]), "=f"(d[5]), "=f"(d[6]), "=f"(d[7]), "=f"(d[8]), "=f"(d[9]), "=f"(d[10]), "=f"(d[11]), "=f"(d[12]), "=f"(d[13]), "=f"(d[14]), "=f"(d[15]), "=f"(d[16]), "=f"(d[17]), "=f"(d[18]), "=f"(d[19]), "=f"(d[20]), "=f"(d[21]), "=f"(d[22]), "=f"(d[23]), "=f"(d[24]), "=f"(d[25]), "=f"(d[26]), "=f"(d[27]), "=f"(d[28]), "=f"(d[29]), "=f"(d[30]), "=f"(d[31]), "=f"(d[32]), "=f"(d[33]), "=f"(d[34]), "=f"(d[35]), "=f"(d[36]), "=f"(d[37]), "=f"(d[38]), "=f"(d[39]), "=f"(d[40]), "=f"(d[41]), "=f"(d[42]), "=f"(d[43]), "=f"(d[44]), "=f"(d[45]), "=f"(d[46]), "=f"(d[47]), "=f"(d[48]), "=f"(d[49]), "=f"(d[50]), "=f"(d[51]), "=f"(d[52]), "=f"(d[53]), "=f"(d[54]), "=f"(d[55]), "=f"(d[56]), "=f"(d[57]), "=f"(d[58]), "=f"(d[59]), "=f"(d[60]), "=f"(d[61]), "=f"(d[62]), "=f"(d[63])
      : "l"(da), "l"(db), "n"(TA), "n"(TB));
  }
};
template<int TA, int TB> struct WgSS<192, TA, TB> {
  static __device__ __forceinline__ void mma(float (&d)[96], uint64_t da, uint64_t db, int sd) {
    asm volatile("{\n.reg .pred p;\nsetp.ne.b32 p, %98, 0;\n"
      "wgmma.mma_async.sync.aligned.m64n192k16.f32.bf16.bf16 {%0, %1, %2, %3, %4, %5, %6, %7, %8, %9, %10, %11, %12, %13, %14, %15, %16, %17, %18, %19, %20, %21, %22, %23, %24, %25, %26, %27, %28, %29, %30, %31, %32, %33, %34, %35, %36, %37, %38, %39, %40, %41, %42, %43, %44, %45, %46, %47, %48, %49, %50, %51, %52, %53, %54, %55, %56, %57, %58, %59, %60, %61, %62, %63, %64, %65, %66, %67, %68, %69, %70, %71, %72, %73, %74, %75, %76, %77, %78, %79, %80, %81, %82, %83, %84, %85, %86, %87, %88, %89, %90, %91, %92, %93, %94, %95}, %96, %97, p, 1, 1, %99, %100;\n}\n"
      : "+f"(d[0]), "+f"(d[1]), "+f"(d[2]), "+f"(d[3]), "+f"(d[4]), "+f"(d[5]), "+f"(d[6]), "+f"(d[7]), "+f"(d[8]), "+f"(d[9]), "+f"(d[10]), "+f"(d[11]), "+f"(d[12]), "+f"(d[13]), "+f"(d[14]), "+f"(d[15]), "+f"(d[16]), "+f"(d[17]), "+f"(d[18]), "+f"(d[19]), "+f"(d[20]), "+f"(d[21]), "+f"(d[22]), "+f"(d[23]), "+f"(d[24]), "+f"(d[25]), "+f"(d[26]), "+f"(d[27]), "+f"(d[28]), "+f"(d[29]), "+f"(d[30]), "+f"(d[31]), "+f"(d[32]), "+f"(d[33]), "+f"(d[34]), "+f"(d[35]), "+f"(d[36]), "+f"(d[37]), "+f"(d[38]), "+f"(d[39]), "+f"(d[40]), "+f"(d[41]), "+f"(d[42]), "+f"(d[43]), "+f"(d[44]), "+f"(d[45]), "+f"(d[46]), "+f"(d[47]), "+f"(d[48]), "+f"(d[49]), "+f"(d[50]), "+f"(d[51]), "+f"(d[52]), "+f"(d[53]), "+f"(d[54]), "+f"(d[55]), "+f"(d[56]), "+f"(d[57]), "+f"(d[58]), "+f"(d[59]), "+f"(d[60]), "+f"(d[61]), "+f"(d[62]), "+f"(d[63]), "+f"(d[64]), "+f"(d[65]), "+f"(d[66]), "+f"(d[67]), "+f"(d[68]), "+f"(d[69]), "+f"(d[70]), "+f"(d[71]), "+f"(d[72]), "+f"(d[73]), "+f"(d[74]), "+f"(d[75]), "+f"(d[76]), "+f"(d[77]), "+f"(d[78]), "+f"(d[79]), "+f"(d[80]), "+f"(d[81]), "+f"(d[82]), "+f"(d[83]), "+f"(d[84]), "+f"(d[85]), "+f"(d[86]), "+f"(d[87]), "+f"(d[88]), "+f"(d[89]), "+f"(d[90]), "+f"(d[91]), "+f"(d[92]), "+f"(d[93]), "+f"(d[94]), "+f"(d[95])
      : "l"(da), "l"(db), "r"(sd), "n"(TA), "n"(TB));
  }
  static __device__ __forceinline__ void mma0(float (&d)[96], uint64_t da, uint64_t db) {
    asm volatile("{\n.reg .pred p;\nsetp.ne.b32 p, 0, 0;\n"
      "wgmma.mma_async.sync.aligned.m64n192k16.f32.bf16.bf16 {%0, %1, %2, %3, %4, %5, %6, %7, %8, %9, %10, %11, %12, %13, %14, %15, %16, %17, %18, %19, %20, %21, %22, %23, %24, %25, %26, %27, %28, %29, %30, %31, %32, %33, %34, %35, %36, %37, %38, %39, %40, %41, %42, %43, %44, %45, %46, %47, %48, %49, %50, %51, %52, %53, %54, %55, %56, %57, %58, %59, %60, %61, %62, %63, %64, %65, %66, %67, %68, %69, %70, %71, %72, %73, %74, %75, %76, %77, %78, %79, %80, %81, %82, %83, %84, %85, %86, %87, %88, %89, %90, %91, %92, %93, %94, %95}, %96, %97, p, 1, 1, %98, %99;\n}\n"
      : "=f"(d[0]), "=f"(d[1]), "=f"(d[2]), "=f"(d[3]), "=f"(d[4]), "=f"(d[5]), "=f"(d[6]), "=f"(d[7]), "=f"(d[8]), "=f"(d[9]), "=f"(d[10]), "=f"(d[11]), "=f"(d[12]), "=f"(d[13]), "=f"(d[14]), "=f"(d[15]), "=f"(d[16]), "=f"(d[17]), "=f"(d[18]), "=f"(d[19]), "=f"(d[20]), "=f"(d[21]), "=f"(d[22]), "=f"(d[23]), "=f"(d[24]), "=f"(d[25]), "=f"(d[26]), "=f"(d[27]), "=f"(d[28]), "=f"(d[29]), "=f"(d[30]), "=f"(d[31]), "=f"(d[32]), "=f"(d[33]), "=f"(d[34]), "=f"(d[35]), "=f"(d[36]), "=f"(d[37]), "=f"(d[38]), "=f"(d[39]), "=f"(d[40]), "=f"(d[41]), "=f"(d[42]), "=f"(d[43]), "=f"(d[44]), "=f"(d[45]), "=f"(d[46]), "=f"(d[47]), "=f"(d[48]), "=f"(d[49]), "=f"(d[50]), "=f"(d[51]), "=f"(d[52]), "=f"(d[53]), "=f"(d[54]), "=f"(d[55]), "=f"(d[56]), "=f"(d[57]), "=f"(d[58]), "=f"(d[59]), "=f"(d[60]), "=f"(d[61]), "=f"(d[62]), "=f"(d[63]), "=f"(d[64]), "=f"(d[65]), "=f"(d[66]), "=f"(d[67]), "=f"(d[68]), "=f"(d[69]), "=f"(d[70]), "=f"(d[71]), "=f"(d[72]), "=f"(d[73]), "=f"(d[74]), "=f"(d[75]), "=f"(d[76]), "=f"(d[77]), "=f"(d[78]), "=f"(d[79]), "=f"(d[80]), "=f"(d[81]), "=f"(d[82]), "=f"(d[83]), "=f"(d[84]), "=f"(d[85]), "=f"(d[86]), "=f"(d[87]), "=f"(d[88]), "=f"(d[89]), "=f"(d[90]), "=f"(d[91]), "=f"(d[92]), "=f"(d[93]), "=f"(d[94]), "=f"(d[95])
      : "l"(da), "l"(db), "n"(TA), "n"(TB));
  }
};
template<int TB> struct WgRS<64, TB> {
  static __device__ __forceinline__ void mma(float (&d)[32], uint32_t a0, uint32_t a1, uint32_t a2, uint32_t a3, uint64_t db, int sd) {
    asm volatile("{\n.reg .pred p;\nsetp.ne.b32 p, %37, 0;\n"
      "wgmma.mma_async.sync.aligned.m64n64k16.f32.bf16.bf16 {%0, %1, %2, %3, %4, %5, %6, %7, %8, %9, %10, %11, %12, %13, %14, %15, %16, %17, %18, %19, %20, %21, %22, %23, %24, %25, %26, %27, %28, %29, %30, %31}, {%32, %33, %34, %35}, %36, p, 1, 1, %38;\n}\n"
      : "+f"(d[0]), "+f"(d[1]), "+f"(d[2]), "+f"(d[3]), "+f"(d[4]), "+f"(d[5]), "+f"(d[6]), "+f"(d[7]), "+f"(d[8]), "+f"(d[9]), "+f"(d[10]), "+f"(d[11]), "+f"(d[12]), "+f"(d[13]), "+f"(d[14]), "+f"(d[15]), "+f"(d[16]), "+f"(d[17]), "+f"(d[18]), "+f"(d[19]), "+f"(d[20]), "+f"(d[21]), "+f"(d[22]), "+f"(d[23]), "+f"(d[24]), "+f"(d[25]), "+f"(d[26]), "+f"(d[27]), "+f"(d[28]), "+f"(d[29]), "+f"(d[30]), "+f"(d[31])
      : "r"(a0), "r"(a1), "r"(a2), "r"(a3), "l"(db), "r"(sd), "n"(TB));
  }
  static __device__ __forceinline__ void mma0(float (&d)[32], uint32_t a0, uint32_t a1, uint32_t a2, uint32_t a3, uint64_t db) {
    asm volatile("{\n.reg .pred p;\nsetp.ne.b32 p, 0, 0;\n"
      "wgmma.mma_async.sync.aligned.m64n64k16.f32.bf16.bf16 {%0, %1, %2, %3, %4, %5, %6, %7, %8, %9, %10, %11, %12, %13, %14, %15, %16, %17, %18, %19, %20, %21, %22, %23, %24, %25, %26, %27, %28, %29, %30, %31}, {%32, %33, %34, %35}, %36, p, 1, 1, %37;\n}\n"
      : "=f"(d[0]), "=f"(d[1]), "=f"(d[2]), "=f"(d[3]), "=f"(d[4]), "=f"(d[5]), "=f"(d[6]), "=f"(d[7]), "=f"(d[8]), "=f"(d[9]), "=f"(d[10]), "=f"(d[11]), "=f"(d[12]), "=f"(d[13]), "=f"(d[14]), "=f"(d[15]), "=f"(d[16]), "=f"(d[17]), "=f"(d[18]), "=f"(d[19]), "=f"(d[20]), "=f"(d[21]), "=f"(d[22]), "=f"(d[23]), "=f"(d[24]), "=f"(d[25]), "=f"(d[26]), "=f"(d[27]), "=f"(d[28]), "=f"(d[29]), "=f"(d[30]), "=f"(d[31])
      : "r"(a0), "r"(a1), "r"(a2), "r"(a3), "l"(db), "n"(TB));
  }
};
template<int TB> struct WgRS<128, TB> {
  static __device__ __forceinline__ void mma(float (&d)[64], uint32_t a0, uint32_t a1, uint32_t a2, uint32_t a3, uint64_t db, int sd) {
    asm volatile("{\n.reg .pred p;\nsetp.ne.b32 p, %69, 0;\n"
      "wgmma.mma_async.sync.aligned.m64n128k16.f32.bf16.bf16 {%0, %1, %2, %3, %4, %5, %6, %7, %8, %9, %10, %11, %12, %13, %14, %15, %16, %17, %18, %19, %20, %21, %22, %23, %24, %25, %26, %27, %28, %29, %30, %31, %32, %33, %34, %35, %36, %37, %38, %39, %40, %41, %42, %43, %44, %45, %46, %47, %48, %49, %50, %51, %52, %53, %54, %55, %56, %57, %58, %59, %60, %61, %62, %63}, {%64, %65, %66, %67}, %68, p, 1, 1, %70;\n}\n"
      : "+f"(d[0]), "+f"(d[1]), "+f"(d[2]), "+f"(d[3]), "+f"(d[4]), "+f"(d[5]), "+f"(d[6]), "+f"(d[7]), "+f"(d[8]), "+f"(d[9]), "+f"(d[10]), "+f"(d[11]), "+f"(d[12]), "+f"(d[13]), "+f"(d[14]), "+f"(d[15]), "+f"(d[16]), "+f"(d[17]), "+f"(d[18]), "+f"(d[19]), "+f"(d[20]), "+f"(d[21]), "+f"(d[22]), "+f"(d[23]), "+f"(d[24]), "+f"(d[25]), "+f"(d[26]), "+f"(d[27]), "+f"(d[28]), "+f"(d[29]), "+f"(d[30]), "+f"(d[31]), "+f"(d[32]), "+f"(d[33]), "+f"(d[34]), "+f"(d[35]), "+f"(d[36]), "+f"(d[37]), "+f"(d[38]), "+f"(d[39]), "+f"(d[40]), "+f"(d[41]), "+f"(d[42]), "+f"(d[43]), "+f"(d[44]), "+f"(d[45]), "+f"(d[46]), "+f"(d[47]), "+f"(d[48]), "+f"(d[49]), "+f"(d[50]), "+f"(d[51]), "+f"(d[52]), "+f"(d[53]), "+f"(d[54]), "+f"(d[55]), "+f"(d[56]), "+f"(d[57]), "+f"(d[58]), "+f"(d[59]), "+f"(d[60]), "+f"(d[61]), "+f"(d[62]), "+f"(d[63])
      : "r"(a0), "r"(a1), "r"(a2), "r"(a3), "l"(db), "r"(sd), "n"(TB));
  }
  static __device__ __forceinline__ void mma0(float (&d)[64], uint32_t a0, uint32_t a1, uint32_t a2, uint32_t a3, uint64_t db) {
    asm volatile("{\n.reg .pred p;\nsetp.ne.b32 p, 0, 0;\n"
      "wgmma.mma_async.sync.aligned.m64n128k16.f32.bf16.bf16 {%0, %1, %2, %3, %4, %5, %6, %7, %8, %9, %10, %11, %12, %13, %14, %15, %16, %17, %18, %19, %20, %21, %22, %23, %24, %25, %26, %27, %28, %29, %30, %31, %32, %33, %34, %35, %36, %37, %38, %39, %40, %41, %42, %43, %44, %45, %46, %47, %48, %49, %50, %51, %52, %53, %54, %55, %56, %57, %58, %59, %60, %61, %62, %63}, {%64, %65, %66, %67}, %68, p, 1, 1, %69;\n}\n"
      : "=f"(d[0]), "=f"(d[1]), "=f"(d[2]), "=f"(d[3]), "=f"(d[4]), "=f"(d[5]), "=f"(d[6]), "=f"(d[7]), "=f"(d[8]), "=f"(d[9]), "=f"(d[10]), "=f"(d[11]), "=f"(d[12]), "=f"(d[13]), "=f"(d[14]), "=f"(d[15]), "=f"(d[16]), "=f"(d[17]), "=f"(d[18]), "=f"(d[19]), "=f"(d[20]), "=f"(d[21]), "=f"(d[22]), "=f"(d[23]), "=f"(d[24]), "=f"(d[25]), "=f"(d[26]), "=f"(d[27]), "=f"(d[28]), "=f"(d[29]), "=f"(d[30]), "=f"(d[31]), "=f"(d[32]), "=f"(d[33]), "=f"(d[34]), "=f"(d[35]), "=f"(d[36]), "=f"(d[37]), "=f"(d[38]), "=f"(d[39]), "=f"(d[40]), "=f"(d[41]), "=f"(d[42]), "=f"(d[43]), "=f"(d[44]), "=f"(d[45]), "=f"(d[46]), "=f"(d[47]), "=f"(d[48]), "=f"(d[49]), "=f"(d[50]), "=f"(d[51]), "=f"(d[52]), "=f"(d[53]), "=f"(d[54]), "=f"(d[55]), "=f"(d[56]), "=f"(d[57]), "=f"(d[58]), "=f"(d[59]), "=f"(d[60]), "=f"(d[61]), "=f"(d[62]), "=f"(d[63])
      : "r"(a0), "r"(a1), "r"(a2), "r"(a3), "l"(db), "n"(TB));
  }
};

namespace {

constexpr int B_ = 32, SQ = 160, D_ = 640, H_ = 32, SK = 512, DH = 128;
constexpr int NSLOT = 5;
constexpr int SLOT = 32768;
constexpr int OFF_STASH = NSLOT * SLOT;
constexpr int OFF_QL = OFF_STASH + 32768;
constexpr int OFF_PT = OFF_QL + 16384;
constexpr int OFF_RED = OFF_PT + 16384;
constexpr int OFF_BAR = OFF_RED + 1024;
constexpr int OFF_ALPHA = OFF_BAR + 768;
constexpr int SMEM_BYTES = OFF_ALPHA + 1280;
constexpr uint32_t ONS0 = 8, ONS1 = 11, ONS2 = 13;
constexpr int NPAIR = 66, NJOB = 250, NPSLOT = 80;
constexpr int A_TILE = 12288;
constexpr int O_PLANE = B_ * SQ * 16;
#define OAL(b) (b)
#define OALR(rt) (rt)
#define OALH(h) (h)
#define PF_MASK 0x0492
#define NTMPF 10
#define PRE2 0
#define PRE2W 3
#define PRE2NS 1000
#define FLAGSEM "release"
#define RDYV 3
#define QPACE 200
#define XSLEEP2 100
#define CA 2
#define CB 5
#define PREW 1
#define TLBW 1
#define TLBM 255
#define PRE_ALL 0
#define PRE_ROWS 160
#define PF_WIN 2
#define PF_GO 15
#define PFD 0
#define TPOS 4
#define WPOS 8
#define SPLIT 1
#define WPOS2 WPOS
#define XSLEEP 40
#define DISCARD 1
#define OEF_T 1
#define ORDER 0
#define LAGST 19
#define NPRE 2
#define KV_DEPTH 2
constexpr int RESCALE_THR_BITS = 0x41000000;
constexpr float RESCALE_THR = 8.0f;
constexpr uint32_t LOW_THR_BITS = 0xc3680000u;
constexpr float SUM_HI = 65536.f, SUM_LO = 1.f / 67108864.f;
constexpr uint32_t HI2 = 0x47804780u, LO2 = 0x32803280u;
constexpr float SCALE_LOG2 = 0.08838834764831845f * 1.4426950408889634f;

__device__ __align__(1024) __nv_bfloat16 g_o[(size_t)B_ * SQ * H_ * DH];
__device__ uint4 g_part[(size_t)NPSLOT * 2 * 2048];
__device__ unsigned int g_oflag[B_ * H_ + 640];
__device__ unsigned int g_oread[40 * H_];
__device__ unsigned long long g_ticket;
__device__ unsigned int g_queue;
constexpr uint32_t XST = 0x3060;
constexpr uint32_t J_DUMMY = 8, J_CLAIM = 0x1000, J_LAST = 0x2000;
constexpr uint32_t J_Q3 = 0x2000, J_PRE = 0x4000, J_ATO = 0x8000, J_QO = 4, Q_BYTES = 81920, QFLAG = 16 * H_ + 1;
__device__ __align__(128) uint8_t g_q[(size_t)64 * 2 * Q_BYTES];

constexpr uint32_t NB0 = 7, NH0 = 8;
constexpr uint32_t QBASE = 98, NQUEUE = 238, NCLAIM = 242;
__constant__ uint4 c_all[337] = {
  {0x2d21001, 0x0, 0x10442, 0x0}, {0x1925561, 0xff0, 0x0, 0x2ee0}, {0x1904855, 0x10840, 0x0, 0x0}, {0x2d21061, 0x0, 0x10442, 0x0},
  {0x1925651, 0x30ef0, 0x0, 0x2ee0}, {0x2d21231, 0x0, 0x10442, 0x0}, {0x1904a85, 0x40a70, 0x0, 0x0}, {0x2d21601, 0x0, 0x10442, 0x0},
  {0x1925751, 0x60df0, 0x0, 0x2ee0}, {0x2d21451, 0x0, 0x10442, 0x0}, {0x2d20011, 0x0, 0x12a52, 0x0}, {0x1925801, 0x70cf0, 0x0, 0x2ee0},
  {0x2d21301, 0x0, 0x10442, 0x0}, {0x2d21141, 0x0, 0x10442, 0x0}, {0x2d20241, 0x0, 0x12a52, 0x0}, {0x1925721, 0x80bf0, 0x0, 0x2ee0},
  {0x2d21321, 0x0, 0x10442, 0x0}, {0x1925761, 0x90af0, 0x0, 0x2ee0}, {0x2d20461, 0x0, 0x12a52, 0x0}, {0x2d21101, 0x0, 0x10442, 0x0},
  {0x2d21211, 0x0, 0x10442, 0x0}, {0x1925621, 0xa09f0, 0x0, 0x2ee0}, {0x2d20311, 0x0, 0x12a52, 0x0}, {0x2d21151, 0x0, 0x10442, 0x0},
  {0x1925901, 0xb08f0, 0x0, 0x2ee0}, {0x2d21331, 0x0, 0x10442, 0x0}, {0x2d20611, 0x0, 0x12a52, 0x0}, {0x2d21701, 0x0, 0x10442, 0x0},
  {0x1925821, 0xc07f0, 0x0, 0x2ee0}, {0x2d21111, 0x0, 0x10442, 0x0}, {0x2d20021, 0x0, 0x12a52, 0x0}, {0x1925631, 0xd06f0, 0x0, 0x2ee0},
  {0x2d21161, 0x0, 0x10442, 0x0}, {0x2d21251, 0x0, 0x10442, 0x0}, {0x1925731, 0xe05f0, 0x0, 0x2ee0}, {0x2d20341, 0x0, 0x12a52, 0x0},
  {0x2d21421, 0x0, 0x10442, 0x0}, {0x1925831, 0xf04f0, 0x0, 0x2ee0}, {0x2d21201, 0x0, 0x10442, 0x0}, {0x2d20031, 0x0, 0x12a52, 0x0},
  {0x2d21121, 0x0, 0x10442, 0x0}, {0x1925661, 0x1003f0, 0x0, 0x2ee0}, {0x2d21401, 0x0, 0x10442, 0x0}, {0x2d20261, 0x0, 0x12a52, 0x0},
  {0x1925741, 0x1102f0, 0x0, 0x2ee0}, {0x2d21431, 0x0, 0x10442, 0x0}, {0x2d21711, 0x0, 0x10442, 0x0}, {0x2d20521, 0x0, 0x12a52, 0x0},
  {0x1925811, 0x1201f0, 0x0, 0x2ee0}, {0x2d21041, 0x0, 0x10442, 0x0}, {0x1925641, 0x1300f0, 0x0, 0x2ee0}, {0x2d20411, 0x0, 0x12a52, 0x0},
  {0x2d21501, 0x0, 0x10442, 0x0}, {0x2d21351, 0x0, 0x10442, 0x0}, {0x1925a01, 0x140ce0, 0x0, 0x2ee0}, {0x2d20441, 0x0, 0x12a52, 0x0},
  {0x2d21531, 0x0, 0x10442, 0x0}, {0x1925551, 0x150cd0, 0x0, 0x2ee0}, {0x2d21051, 0x0, 0x10442, 0x0}, {0x2d20131, 0x0, 0x12a52, 0x0},
  {0x2d21221, 0x0, 0x10442, 0x0}, {0x1925911, 0x160aa0, 0x0, 0x2ee0}, {0x2d21511, 0x0, 0x10442, 0x0}, {0x2d20361, 0x0, 0x12a52, 0x0},
  {0x1925a11, 0x170a90, 0x0, 0x2ee0}, {0x2d21541, 0x0, 0x10442, 0x0}, {0x1000002, 0x0, 0x0, 0x5}, {0x1002052, 0x0, 0x0, 0x1000},
  {0x1000002, 0x50000, 0x0, 0x5}, {0x1002052, 0x50000, 0x0, 0x1000}, {0x10000a2, 0x0, 0x0, 0x2004}, {0x10020f2, 0x0, 0x0, 0x3000},
  {0x10000a2, 0x50000, 0x0, 0x2004}, {0x10020f2, 0x50000, 0x0, 0x3000}, {0x1000012, 0x0, 0x0, 0x4004}, {0x1002062, 0x0, 0x0, 0x5000},
  {0x1000012, 0x50000, 0x0, 0x4004}, {0x1002062, 0x50000, 0x0, 0x5000}, {0x10000b2, 0x0, 0x0, 0x6004}, {0x1002102, 0x0, 0x0, 0x7000},
  {0x10000b2, 0x50000, 0x0, 0x6004}, {0x1002102, 0x50000, 0x0, 0x7000}, {0x1000022, 0x0, 0x0, 0x8004}, {0x1002072, 0x0, 0x0, 0x5000},
  {0x1000022, 0x50000, 0x0, 0x8004}, {0x1002072, 0x50000, 0x0, 0x5000}, {0x10000c2, 0x0, 0x0, 0x9004}, {0x1002112, 0x0, 0x0, 0x7000},
  {0x10000c2, 0x50000, 0x0, 0x9004}, {0x1002112, 0x50000, 0x0, 0x7000}, {0x1000032, 0x0, 0x0, 0xa004}, {0x1002082, 0x0, 0x0, 0xb000},
  {0x1000032, 0x50000, 0x0, 0xa004}, {0x1002082, 0x50000, 0x0, 0xb000}, {0x10000d2, 0x0, 0x0, 0xc004}, {0x1002122, 0x0, 0x0, 0xd000},
  {0x10000d2, 0x50000, 0x0, 0xc004}, {0x1002122, 0x50000, 0x0, 0xd000}, {0x2821861, 0x0, 0x0, 0x0}, {0x2821b01, 0x0, 0x0, 0x0},
  {0x2821b11, 0x0, 0x0, 0x0}, {0x2821921, 0x0, 0x0, 0x0}, {0x2821931, 0x0, 0x0, 0x0}, {0x2821941, 0x0, 0x0, 0x0},
  {0x2821951, 0x0, 0x0, 0x0}, {0x2821961, 0x0, 0x0, 0x0}, {0x2821c01, 0x0, 0x0, 0x0}, {0x2821c11, 0x0, 0x0, 0x0},
  {0x3c79841, 0x10402, 0x0, 0x0}, {0x2821a21, 0x0, 0x0, 0x0}, {0x2821a31, 0x0, 0x0, 0x0}, {0x3c79851, 0x20402, 0x0, 0x0},
  {0x2821a41, 0x0, 0x0, 0x0}, {0x2821a51, 0x0, 0x0, 0x0}, {0x2821a61, 0x0, 0x0, 0x0}, {0x2821d01, 0x0, 0x0, 0x0},
  {0x2821d11, 0x0, 0x0, 0x0}, {0x2821b21, 0x0, 0x0, 0x0}, {0x2821b31, 0x0, 0x0, 0x0}, {0x2821b41, 0x0, 0x0, 0x0},
  {0x2821b51, 0x0, 0x0, 0x0}, {0x2821b61, 0x0, 0x0, 0x0}, {0x2821e01, 0x0, 0x0, 0x0}, {0x2821e11, 0x0, 0x0, 0x0},
  {0x2821c21, 0x0, 0x0, 0x0}, {0x2821c31, 0x0, 0x0, 0x0}, {0x2821c41, 0x0, 0x0, 0x0}, {0x2821c51, 0x0, 0x0, 0x0},
  {0x2821c61, 0x0, 0x0, 0x0}, {0x2821f01, 0x0, 0x0, 0x0}, {0x2821f11, 0x0, 0x0, 0x0}, {0x2821d21, 0x0, 0x0, 0x0},
  {0x2821d31, 0x0, 0x0, 0x0}, {0x2821d41, 0x0, 0x0, 0x0}, {0x2821d51, 0x0, 0x0, 0x0}, {0x2821d61, 0x0, 0x0, 0x0},
  {0x2821e21, 0x0, 0x0, 0x0}, {0x2821e51, 0x0, 0x0, 0x0}, {0x2821e31, 0x0, 0x0, 0x0}, {0x2821e61, 0x0, 0x0, 0x0},
  {0x2821f21, 0x0, 0x0, 0x0}, {0x2821e41, 0x0, 0x0, 0x0}, {0x2821f31, 0x0, 0x0, 0x0}, {0x2821f41, 0x0, 0x0, 0x0},
  {0x2821f51, 0x0, 0x0, 0x0}, {0x2821f61, 0x0, 0x0, 0x0}, {0x2821071, 0x0, 0x0, 0x0}, {0x2821081, 0x0, 0x0, 0x0},
  {0x2821091, 0x0, 0x0, 0x0}, {0x28210a1, 0x0, 0x0, 0x0}, {0x28210b1, 0x0, 0x0, 0x0}, {0x28210c1, 0x0, 0x0, 0x0},
  {0x28210d1, 0x0, 0x0, 0x0}, {0x28210e1, 0x0, 0x0, 0x0}, {0x2821171, 0x0, 0x0, 0x0}, {0x2821181, 0x0, 0x0, 0x0},
  {0x2821191, 0x0, 0x0, 0x0}, {0x28211a1, 0x0, 0x0, 0x0}, {0x28211b1, 0x0, 0x0, 0x0}, {0x28211c1, 0x0, 0x0, 0x0},
  {0x28211d1, 0x0, 0x0, 0x0}, {0x28211e1, 0x0, 0x0, 0x0}, {0x2821271, 0x0, 0x0, 0x0}, {0x2821281, 0x0, 0x0, 0x0},
  {0x2821291, 0x0, 0x0, 0x0}, {0x28212a1, 0x0, 0x0, 0x0}, {0x28212b1, 0x0, 0x0, 0x0}, {0x28212c1, 0x0, 0x0, 0x0},
  {0x28212d1, 0x0, 0x0, 0x0}, {0x28212e1, 0x0, 0x0, 0x0}, {0x2821371, 0x0, 0x0, 0x0}, {0x2821381, 0x0, 0x0, 0x0},
  {0x2821391, 0x0, 0x0, 0x0}, {0x28213a1, 0x0, 0x0, 0x0}, {0x28213b1, 0x0, 0x0, 0x0}, {0x28213c1, 0x0, 0x0, 0x0},
  {0x28213d1, 0x0, 0x0, 0x0}, {0x28213e1, 0x0, 0x0, 0x0}, {0x2821471, 0x0, 0x0, 0x0}, {0x2821481, 0x0, 0x0, 0x0},
  {0x2821491, 0x0, 0x0, 0x0}, {0x28214a1, 0x0, 0x0, 0x0}, {0x28214b1, 0x0, 0x0, 0x0}, {0x28214c1, 0x0, 0x0, 0x0},
  {0x28214d1, 0x0, 0x0, 0x0}, {0x28214e1, 0x0, 0x0, 0x0}, {0x2821571, 0x0, 0x0, 0x0}, {0x2821581, 0x0, 0x0, 0x0},
  {0x2821591, 0x0, 0x0, 0x0}, {0x28215a1, 0x0, 0x0, 0x0}, {0x28215b1, 0x0, 0x0, 0x0}, {0x28215c1, 0x0, 0x0, 0x0},
  {0x28215d1, 0x0, 0x0, 0x0}, {0x28215e1, 0x0, 0x0, 0x0}, {0x2821671, 0x0, 0x0, 0x0}, {0x2821681, 0x0, 0x0, 0x0},
  {0x2821691, 0x0, 0x0, 0x0}, {0x28216a1, 0x0, 0x0, 0x0}, {0x28216b1, 0x0, 0x0, 0x0}, {0x28216c1, 0x0, 0x0, 0x0},
  {0x28216d1, 0x0, 0x0, 0x0}, {0x28216e1, 0x0, 0x0, 0x0}, {0x2821771, 0x0, 0x0, 0x0}, {0x2821781, 0x0, 0x0, 0x0},
  {0x2821791, 0x0, 0x0, 0x0}, {0x28217a1, 0x0, 0x0, 0x0}, {0x28217b1, 0x0, 0x0, 0x0}, {0x28217c1, 0x0, 0x0, 0x0},
  {0x28217d1, 0x0, 0x0, 0x0}, {0x28217e1, 0x0, 0x0, 0x0}, {0x2821871, 0x0, 0x0, 0x0}, {0x2821881, 0x0, 0x0, 0x0},
  {0x2821891, 0x0, 0x0, 0x0}, {0x28218a1, 0x0, 0x0, 0x0}, {0x28218b1, 0x0, 0x0, 0x0}, {0x28218c1, 0x0, 0x0, 0x0},
  {0x28218d1, 0x0, 0x0, 0x0}, {0x28218e1, 0x0, 0x0, 0x0}, {0x10020e2, 0x0, 0x0, 0x3004}, {0x10020e2, 0x50000, 0x0, 0x3004},
  {0x2821971, 0x0, 0x0, 0x0}, {0x2821981, 0x0, 0x0, 0x0}, {0x2821991, 0x0, 0x0, 0x0}, {0x28219a1, 0x0, 0x0, 0x0},
  {0x28219b1, 0x0, 0x0, 0x0}, {0x28219c1, 0x0, 0x0, 0x0}, {0x28219d1, 0x0, 0x0, 0x0}, {0x28219e1, 0x0, 0x0, 0x0},
  {0x2821ab1, 0x0, 0x0, 0x0}, {0x2821ac1, 0x0, 0x0, 0x0}, {0x2821ad1, 0x0, 0x0, 0x0}, {0x2821ae1, 0x0, 0x0, 0x0},
  {0x2821b71, 0x0, 0x0, 0x0}, {0x2821b81, 0x0, 0x0, 0x0}, {0x2821b91, 0x0, 0x0, 0x0}, {0x2821ba1, 0x0, 0x0, 0x0},
  {0x2821bb1, 0x0, 0x0, 0x0}, {0x2821bc1, 0x0, 0x0, 0x0}, {0x2821bd1, 0x0, 0x0, 0x0}, {0x2821be1, 0x0, 0x0, 0x0},
  {0x3c79a71, 0x40406, 0x0, 0x0}, {0x3c79a81, 0x50406, 0x0, 0x0}, {0x3c79a91, 0x170034, 0x0, 0x0}, {0x3c79aa1, 0x160032, 0x0, 0x0},
  {0x2821c71, 0x0, 0x492, 0x0}, {0x2821c81, 0x0, 0x492, 0x0}, {0x2821c91, 0x0, 0x492, 0x0}, {0x2821ca1, 0x0, 0x492, 0x0},
  {0x2821cb1, 0x0, 0x492, 0x0}, {0x2821cc1, 0x0, 0x492, 0x0}, {0x2821d71, 0x0, 0x492, 0x0}, {0x2821d81, 0x0, 0x492, 0x0},
  {0x2821d91, 0x0, 0x492, 0x0}, {0x2821da1, 0x0, 0x492, 0x0}, {0x2821db1, 0x0, 0x492, 0x0}, {0x2821dc1, 0x0, 0x492, 0x0},
  {0x2821dd1, 0x0, 0x492, 0x0}, {0x2821de1, 0x0, 0x492, 0x0}, {0x2821e71, 0x0, 0x492, 0x0}, {0x2821e81, 0x0, 0x492, 0x0},
  {0x2821e91, 0x0, 0x492, 0x0}, {0x2821ea1, 0x0, 0x492, 0x0}, {0x2821eb1, 0x0, 0x492, 0x0}, {0x2821ec1, 0x0, 0x492, 0x0},
  {0x2821ed1, 0x0, 0x492, 0x0}, {0x9002042, 0x0, 0x0, 0x1004}, {0x9002042, 0x30000, 0x0, 0x1004}, {0x2821ee1, 0x0, 0x492, 0x0},
  {0x2821f71, 0x0, 0x492, 0x0}, {0x2821f81, 0x0, 0x492, 0x0}, {0x2821f91, 0x0, 0x492, 0x0}, {0x2821fa1, 0x0, 0x492, 0x0},
  {0x2821fb1, 0x0, 0x492, 0x0}, {0x2821fc1, 0x0, 0x492, 0x0}, {0x2821fd1, 0x0, 0x492, 0x0}, {0x2821fe1, 0x0, 0x492, 0x0},
  {0x3c79cd1, 0x1500aa, 0x0, 0x0}, {0x3c79ce1, 0x140014, 0x0, 0x0}, {0x11002042, 0x60000, 0x0, 0x1004}, {0x11002042, 0x80000, 0x0, 0x1004},
  {0x3c790f1, 0x13008c, 0x0, 0x0}, {0x3c791f1, 0x120030, 0x0, 0x0}, {0x3c792f1, 0x11008e, 0x0, 0x0}, {0x3c793f1, 0x1000cc, 0x0, 0x0},
  {0x3c794f1, 0xf0070, 0x0, 0x0}, {0x3c795f1, 0xe006e, 0x0, 0x0}, {0x3c796f1, 0xd006c, 0x0, 0x0}, {0x3c797f1, 0xc0050, 0x0, 0x0},
  {0x3c798f1, 0xb0012, 0x0, 0x0}, {0x3c799f1, 0xa004c, 0x0, 0x0}, {0x3c79af1, 0x900ce, 0x0, 0x0}, {0x3c79bf1, 0x8004e, 0x0, 0x0},
  {0x3c79cf1, 0x70010, 0x0, 0x0}, {0x3c79df1, 0x600ae, 0x0, 0x0}, {0x3c79ef1, 0x300ac, 0x0, 0x0}, {0x3c79ff1, 0xca, 0x0, 0x0},
  {0x16502092, 0x0, 0x0, 0xe004}, {0x16502092, 0x20404, 0x0, 0xe004}, {0x16502092, 0x40808, 0x0, 0xe004}, {0x16502092, 0x60c0c, 0x0, 0xe004},
  {0x16502092, 0x81010, 0x0, 0xe004}, {0x16502132, 0x1414, 0x0, 0xf004}, {0x16502132, 0x21818, 0x0, 0xf004}, {0x16502132, 0x41c1c, 0x0, 0xf004},
  {0x16502132, 0x62020, 0x0, 0xf004}, {0x16502132, 0x82424, 0x0, 0xf004}, {0x16482092, 0x1, 0x0, 0x10004}, {0x16482092, 0x20405, 0x0, 0x10004},
  {0x16482092, 0x40809, 0x0, 0x10004}, {0x16482092, 0x60c0d, 0x0, 0x10004}, {0x16482092, 0x81011, 0x0, 0x10004}, {0x16482132, 0x1415, 0x0, 0x11004},
  {0x16482132, 0x21819, 0x0, 0x11004}, {0x16482132, 0x41c1d, 0x0, 0x11004}, {0x16482132, 0x62021, 0x0, 0x11004}, {0x16482132, 0x82425, 0x0, 0x11004},
  {0x16382092, 0x2, 0x0, 0x12004}, {0x16382092, 0x20406, 0x0, 0x12004}, {0x16382092, 0x4080a, 0x0, 0x12004}, {0x16382092, 0x60c0e, 0x0, 0x12004},
  {0x16382092, 0x81012, 0x0, 0x12004}, {0x16382132, 0x1416, 0x0, 0x13004}, {0x16382132, 0x2181a, 0x0, 0x13004}, {0x16382132, 0x41c1e, 0x0, 0x13004},
  {0x16382132, 0x62022, 0x0, 0x13004}, {0x16382132, 0x82426, 0x0, 0x13004}, {0x16302092, 0x3, 0x0, 0x14004}, {0x16302092, 0x20407, 0x0, 0x14004},
  {0x16302092, 0x4080b, 0x0, 0x14004}, {0x16302092, 0x60c0f, 0x0, 0x14004}, {0x16302092, 0x81013, 0x0, 0x14004}, {0x16302132, 0x1417, 0x0, 0x15004},
  {0x16302132, 0x2181b, 0x0, 0x15004}, {0x16302132, 0x41c1f, 0x0, 0x15004}, {0x16302132, 0x62023, 0x0, 0x15004}, {0x16302132, 0x82427, 0x0, 0x15004},
  {0x0, 0x0, 0x0, 0x0}};
__constant__ uint4 c_init[NPAIR] = {
  {0x1000000, 0x0, 0x0, 0x2d21001}, {0x1000001, 0x0, 0x0, 0x1925561}, {0x1000002, 0x2060042, 0x3060043, 0x1904855},
  {0x1000003, 0x0, 0x0, 0x2d21061}, {0x1000004, 0x0, 0x0, 0x1925651}, {0x1000005, 0x0, 0x0, 0x2d21231},
  {0x1000006, 0x2060044, 0x3060045, 0x1904a85}, {0x1000007, 0x0, 0x0, 0x2d21601}, {0x1000008, 0x0, 0x0, 0x1925751},
  {0x1000009, 0x0, 0x0, 0x2d21451}, {0x100000a, 0x2020046, 0x3020047, 0x2d20011}, {0x100000b, 0x0, 0x0, 0x1925801},
  {0x100000c, 0x0, 0x0, 0x2d21301}, {0x100000d, 0x0, 0x0, 0x2d21141}, {0x100000e, 0x2020048, 0x3020049, 0x2d20241},
  {0x100000f, 0x0, 0x0, 0x1925721}, {0x1000010, 0x0, 0x0, 0x2d21321}, {0x1000011, 0x0, 0x0, 0x1925761},
  {0x1000012, 0x202004a, 0x302004b, 0x2d20461}, {0x1000013, 0x0, 0x0, 0x2d21101}, {0x1000014, 0x0, 0x0, 0x2d21211},
  {0x1000015, 0x0, 0x0, 0x1925621}, {0x1000016, 0x202004c, 0x302004d, 0x2d20311}, {0x1000017, 0x0, 0x0, 0x2d21151},
  {0x1000018, 0x0, 0x0, 0x1925901}, {0x1000019, 0x0, 0x0, 0x2d21331}, {0x100001a, 0x202004e, 0x302004f, 0x2d20611},
  {0x100001b, 0x0, 0x0, 0x2d21701}, {0x100001c, 0x0, 0x0, 0x1925821}, {0x100001d, 0x0, 0x0, 0x2d21111},
  {0x100001e, 0x2020050, 0x3020051, 0x2d20021}, {0x100001f, 0x0, 0x0, 0x1925631}, {0x1000020, 0x0, 0x0, 0x2d21161},
  {0x1000021, 0x0, 0x0, 0x2d21251}, {0x1000022, 0x0, 0x0, 0x1925731}, {0x1000023, 0x2020052, 0x3020053, 0x2d20341},
  {0x1000024, 0x0, 0x0, 0x2d21421}, {0x1000025, 0x0, 0x0, 0x1925831}, {0x1000026, 0x0, 0x0, 0x2d21201},
  {0x1000027, 0x2020054, 0x3020055, 0x2d20031}, {0x1000028, 0x0, 0x0, 0x2d21121}, {0x1000029, 0x0, 0x0, 0x1925661},
  {0x100002a, 0x0, 0x0, 0x2d21401}, {0x100002b, 0x2020056, 0x3020057, 0x2d20261}, {0x100002c, 0x0, 0x0, 0x1925741},
  {0x100002d, 0x0, 0x0, 0x2d21431}, {0x100002e, 0x0, 0x0, 0x2d21711}, {0x100002f, 0x2020058, 0x3020059, 0x2d20521},
  {0x1000030, 0x0, 0x0, 0x1925811}, {0x1000031, 0x0, 0x0, 0x2d21041}, {0x1000032, 0x0, 0x0, 0x1925641},
  {0x1000033, 0x202005a, 0x302005b, 0x2d20411}, {0x1000034, 0x0, 0x0, 0x2d21501}, {0x1000035, 0x0, 0x0, 0x2d21351},
  {0x1000036, 0x0, 0x0, 0x1925a01}, {0x1000037, 0x202005c, 0x302005d, 0x2d20441}, {0x1000038, 0x0, 0x0, 0x2d21531},
  {0x1000039, 0x0, 0x0, 0x1925551}, {0x100003a, 0x0, 0x0, 0x2d21051}, {0x100003b, 0x202005e, 0x302005f, 0x2d20131},
  {0x100003c, 0x0, 0x0, 0x2d21221}, {0x100003d, 0x0, 0x0, 0x1925911}, {0x100003e, 0x0, 0x0, 0x2d21511},
  {0x100003f, 0x2020060, 0x3020061, 0x2d20361}, {0x1000040, 0x0, 0x0, 0x1925a11}, {0x1000041, 0x0, 0x0, 0x2d21541}};
__constant__ uint8_t c_order[22][32] = {
  {0,2,4,6,8,10,12,14,1,3,5,7,9,11,13,15,16,18,20,17,19,21,22,24,26,28,23,25,27,29,30,31},
  {0,1,2,4,6,3,5,7,8,10,12,9,11,13,14,16,18,20,15,17,19,21,22,24,23,25,26,28,30,27,29,31},
  {1,3,5,7,9,11,13,15,0,2,4,6,8,10,12,14,17,19,21,16,18,20,23,25,27,29,22,24,26,28,31,30},
  {1,0,3,5,7,2,4,6,9,11,13,8,10,12,15,17,19,21,14,16,18,20,23,25,22,24,27,29,31,26,28,30},
  {0,2,4,6,8,10,1,3,5,7,9,11,12,14,16,13,15,17,18,20,22,24,19,21,23,25,26,28,30,27,29,31},
  {0,2,4,6,1,3,5,7,8,10,9,11,12,13,14,16,18,15,17,19,20,22,21,23,24,25,26,28,30,27,29,31},
  {1,3,5,7,9,11,0,2,4,6,8,10,13,15,17,12,14,16,19,21,23,25,18,20,22,24,27,29,31,26,28,30},
  {1,3,5,7,0,2,4,6,9,11,8,10,13,12,15,17,19,14,16,18,21,23,20,22,25,24,27,29,31,26,28,30},
  {0,2,4,6,8,10,1,3,5,7,9,11,12,14,13,15,16,17,18,20,22,24,19,21,23,25,26,28,30,27,29,31},
  {1,3,5,7,9,11,0,2,4,6,8,10,13,15,12,14,17,16,19,21,23,25,18,20,22,24,27,29,31,26,28,30},
  {0,2,4,6,8,1,3,5,7,9,10,12,14,11,13,15,16,18,20,22,17,19,21,23,24,26,28,30,25,27,29,31},
  {0,2,4,6,1,3,5,7,8,10,9,11,12,14,16,18,13,15,17,19,20,22,21,23,24,26,25,28,30,27,29,31},
  {1,3,5,7,9,0,2,4,6,8,11,13,15,10,12,14,17,19,21,23,16,18,20,22,25,27,29,31,24,26,28,30},
  {1,3,5,7,0,2,4,6,9,11,8,10,13,15,17,19,12,14,16,18,21,23,20,22,25,27,24,29,31,26,28,30},
  {0,4,8,14,22,30,7,15,23,31,0,0,0,0,0,0,0,0,0,0,0,0,0,0,0,0,0,0,0,0,0,0},
  {1,5,9,15,23,31,6,14,22,30,0,0,0,0,0,0,0,0,0,0,0,0,0,0,0,0,0,0,0,0,0,0},
  {2,6,12,20,28,5,13,21,29,0,0,0,0,0,0,0,0,0,0,0,0,0,0,0,0,0,0,0,0,0,0,0},
  {3,7,13,21,29,4,12,20,28,0,0,0,0,0,0,0,0,0,0,0,0,0,0,0,0,0,0,0,0,0,0,0},
  {10,16,24,1,9,17,25,0,0,0,0,0,0,0,0,0,0,0,0,0,0,0,0,0,0,0,0,0,0,0,0,0},
  {11,17,25,0,8,16,24,0,0,0,0,0,0,0,0,0,0,0,0,0,0,0,0,0,0,0,0,0,0,0,0,0},
  {18,26,3,11,19,27,0,0,0,0,0,0,0,0,0,0,0,0,0,0,0,0,0,0,0,0,0,0,0,0,0,0},
  {19,27,2,10,18,26,0,0,0,0,0,0,0,0,0,0,0,0,0,0,0,0,0,0,0,0,0,0,0,0,0,0}};

#define PROF_T(tag) do {} while (0)
#define PROF_F(tag) do {} while (0)
#define PROF_H(i) do {} while (0)
#define PROF_M(i) do {} while (0)
#define PROF_DUMP() do {} while (0)
__device__ __forceinline__ uint32_t smem_u32(const void* p) { return (uint32_t)__cvta_generic_to_shared(p); }
__device__ __forceinline__ void mbar_init(uint32_t bar, int cnt) {
  asm volatile("mbarrier.init.shared::cta.b64 [%0], %1;" ::"r"(bar), "r"(cnt));
}
__device__ __forceinline__ void mbar_expect_tx(uint32_t bar, uint32_t bytes) {
  asm volatile("mbarrier.arrive.expect_tx.shared::cta.b64 _, [%0], %1;" ::"r"(bar), "r"(bytes) : "memory");
}
__device__ __forceinline__ void mbar_wait(uint32_t bar, uint32_t parity) {
  asm volatile(
      "{\n.reg .pred p;\n.reg .u32 n;\n"
      "mbarrier.try_wait.parity.shared::cta.b64 p, [%0], %1;\n"
      "@p bra LD;\n"
      "mov.u32 n, 0;\n"
      "LW:\n"
      "mbarrier.try_wait.parity.shared::cta.b64 p, [%0], %1;\n"
      "@p bra LD;\n"
      "add.u32 n, n, 1;\n"
      "setp.gt.u32 p, n, 4000000;\n"
      "@p trap;\n"
      "bra LW;\n"
      "LD:\n}\n" ::"r"(bar), "r"(parity) : "memory");
}
__device__ __forceinline__ bool mbar_test(uint32_t bar, uint32_t parity) {
  uint32_t r;
  asm volatile("{\n.reg .pred p;\nmbarrier.test_wait.parity.shared::cta.b64 p, [%1], %2;\nselp.u32 %0, 1, 0, p;\n}\n"
               : "=r"(r) : "r"(bar), "r"(parity) : "memory");
  return __all_sync(0xffffffffu, r != 0);
}
__device__ __forceinline__ void mbar_wait_soft(uint32_t bar, uint32_t parity) {
  asm volatile(
      "{\n.reg .pred p;\n.reg .u32 n;\n"
      "mov.u32 n, 0;\n"
      "LW:\n"
      "mbarrier.try_wait.parity.shared::cta.b64 p, [%0], %1;\n"
      "@p bra LD;\n"
      "add.u32 n, n, 1;\n"
      "setp.lt.u32 p, n, 20000;\n"
      "@p bra LW;\n"
      "LD:\n}\n" ::"r"(bar), "r"(parity) : "memory");
}
template <bool SLEEP> __device__ __forceinline__ void flag_wait(const unsigned int* p, uint32_t target) {
  asm volatile(
      "{\n.reg .pred p;\n.reg .u32 n;\n.reg .s32 v;\n"
      "mov.u32 n, 0;\n"
      "LW:\n"
      "ld.acquire.gpu.global.s32 v, [%0];\n"
      "sub.s32 v, v, %1;\n"
      "setp.ge.s32 p, v, 0;\n"
      "@p bra LD;\n"
      "nanosleep.u32 %2;\n"
      "add.u32 n, n, 1;\n"
      "setp.gt.u32 p, n, 4000000;\n"
      "@p trap;\n"
      "bra LW;\n"
      "LD:\n}\n" ::"l"(p), "r"(target), "n"(SLEEP ? 100 : 0) : "memory");
}
__device__ __forceinline__ uint32_t epoch_get(uint32_t addr) {
  uint32_t v;
  asm volatile(
      "{\n.reg .pred p;\n.reg .u32 n, t;\n"
      "mov.u32 n, 0;\n"
      "LW:\n"
      "ld.volatile.shared.v2.u32 {%0, t}, [%1];\n"
      "setp.ne.u32 p, t, 0;\n"
      "@p bra LD;\n"
      "add.u32 n, n, 1;\n"
      "setp.gt.u32 p, n, 40000000;\n"
      "@p trap;\n"
      "bra LW;\n"
      "LD:\n}\n" : "=r"(v) : "r"(addr) : "memory");
  return v;
}
template <int NS = 40> __device__ __forceinline__ uint32_t job_get(uint32_t addr, int ji) {
  uint32_t v;
  asm volatile(
      "{\n.reg .pred p;\n.reg .u32 n, t;\n"
      "mov.u32 n, 0;\n"
      "LW:\n"
      "ld.volatile.shared.u32 %0, [%1];\n"
      "shr.u32 t, %0, 24;\n"
      "setp.eq.u32 p, t, %2;\n"
      "@p bra LD;\n"
      "nanosleep.u32 %3;\n"
      "add.u32 n, n, 1;\n"
      "setp.gt.u32 p, n, 40000000;\n"
      "@p trap;\n"
      "bra LW;\n"
      "LD:\n}\n" : "=r"(v) : "r"(addr + (ji & 7) * 4), "r"(ji + 1), "n"(NS) : "memory");
  return __shfl_sync(0xffffffffu, v, 0);
}
__device__ __forceinline__ uint32_t byte_get(uint32_t addr) {
  uint32_t v;
  asm volatile(
      "{\n.reg .pred p;\n.reg .u32 n;\n"
      "mov.u32 n, 0;\n"
      "LW:\n"
      "ld.volatile.shared.u8 %0, [%1];\n"
      "setp.ne.u32 p, %0, 0;\n"
      "@p bra LD;\n"
      "nanosleep.u32 20;\n"
      "add.u32 n, n, 1;\n"
      "setp.gt.u32 p, n, 40000000;\n"
      "@p trap;\n"
      "bra LW;\n"
      "LD:\n}\n" : "=r"(v) : "r"(addr) : "memory");
  return __shfl_sync(0xffffffffu, v, 0);
}
__device__ __forceinline__ uint32_t lds_acquire(uint32_t addr) {
  uint32_t v; asm volatile("ld.acquire.cta.shared.u32 %0, [%1];" : "=r"(v) : "r"(addr) : "memory"); return v;
}
__device__ __forceinline__ void count_wait(uint32_t addr, uint32_t need) {
  asm volatile(
      "{\n.reg .pred p;\n.reg .u32 n, v;\n"
      "mov.u32 n, 0;\n"
      "LW:\n"
      "ld.acquire.cta.shared.u32 v, [%0];\n"
      "setp.ge.u32 p, v, %1;\n"
      "@p bra LD;\n"
      "nanosleep.u32 40;\n"
      "add.u32 n, n, 1;\n"
      "setp.gt.u32 p, n, 40000000;\n"
      "@p trap;\n"
      "bra LW;\n"
      "LD:\n}\n" ::"r"(addr), "r"(need) : "memory");
}
__device__ __forceinline__ void tma_pf_2d(const CUtensorMap* tm, int c0, int c1) {
  asm volatile("cp.async.bulk.prefetch.tensor.2d.L2.global.tile [%0, {%1, %2}];" ::"l"(tm), "r"(c0), "r"(c1) : "memory");
}
__device__ __forceinline__ void tma_pf_3d(const CUtensorMap* tm, int c0, int c1, int c2) {
  asm volatile("cp.async.bulk.prefetch.tensor.3d.L2.global.tile [%0, {%1, %2, %3}];" ::"l"(tm), "r"(c0), "r"(c1), "r"(c2) : "memory");
}
__device__ __forceinline__ void mbar_arrive(uint32_t bar) {
  asm volatile("mbarrier.arrive.shared::cta.b64 _, [%0];" ::"r"(bar) : "memory");
}
__device__ __forceinline__ void tma_store_2d(const CUtensorMap* tm, uint32_t src, int c0, int c1) {
  asm volatile("cp.async.bulk.tensor.2d.global.shared::cta.bulk_group [%0, {%2, %3}], [%1];"
               ::"l"(tm), "r"(src), "r"(c0), "r"(c1) : "memory");
}
__device__ __forceinline__ void fence_async_all() { asm volatile("fence.proxy.async.global;" ::: "memory"); }
__device__ __forceinline__ void mbar_arrive_cluster(uint32_t bar, uint32_t cta) {
  asm volatile("{\n.reg .b32 ra;\nmapa.shared::cluster.u32 ra, %0, %1;\nmbarrier.arrive.shared::cluster.b64 _, [ra];\n}\n"
               ::"r"(bar), "r"(cta) : "memory");
}
__device__ __forceinline__ void tma_2d(uint32_t dst, const CUtensorMap* tm, int c0, int c1, uint32_t bar) {
  asm volatile("cp.async.bulk.tensor.2d.shared::cluster.global.mbarrier::complete_tx::bytes [%0], [%1, {%3, %4}], [%2];"
               ::"r"(dst), "l"(tm), "r"(bar), "r"(c0), "r"(c1) : "memory");
}
__device__ __forceinline__ void tma_2d_hint(uint32_t dst, const CUtensorMap* tm, int c0, int c1, uint32_t bar, uint64_t pol) {
  asm volatile("cp.async.bulk.tensor.2d.shared::cluster.global.mbarrier::complete_tx::bytes.L2::cache_hint [%0], [%1, {%3, %4}], [%2], %5;"
               ::"r"(dst), "l"(tm), "r"(bar), "r"(c0), "r"(c1), "l"(pol) : "memory");
}
__device__ __forceinline__ void tma_store_2d_hint(const CUtensorMap* tm, uint32_t src, int c0, int c1) {
  uint64_t pol;
  asm volatile("createpolicy.fractional.L2::evict_first.b64 %0, 1.0;" : "=l"(pol));
  asm volatile("cp.async.bulk.tensor.2d.global.shared::cta.bulk_group.L2::cache_hint [%0, {%2, %3}], [%1], %4;"
               ::"l"(tm), "r"(src), "r"(c0), "r"(c1), "l"(pol) : "memory");
}
__device__ __forceinline__ void tma_3d_hint(uint32_t dst, const CUtensorMap* tm, int c0, int c1, int c2, uint32_t bar, uint64_t pol) {
  asm volatile("cp.async.bulk.tensor.3d.shared::cluster.global.mbarrier::complete_tx::bytes.L2::cache_hint [%0], [%1, {%3, %4, %5}], [%2], %6;"
               ::"r"(dst), "l"(tm), "r"(bar), "r"(c0), "r"(c1), "r"(c2), "l"(pol) : "memory");
}
__device__ __forceinline__ void tma_2d_mc(uint32_t dst, const CUtensorMap* tm, int c0, int c1, uint32_t bar, uint16_t mask) {
  asm volatile("cp.async.bulk.tensor.2d.shared::cluster.global.mbarrier::complete_tx::bytes.multicast::cluster [%0], [%1, {%3, %4}], [%2], %5;"
               ::"r"(dst), "l"(tm), "r"(bar), "r"(c0), "r"(c1), "h"(mask) : "memory");
}
__device__ __forceinline__ void tma_3d_mc(uint32_t dst, const CUtensorMap* tm, int c0, int c1, int c2, uint32_t bar, uint16_t mask) {
  asm volatile("cp.async.bulk.tensor.3d.shared::cluster.global.mbarrier::complete_tx::bytes.multicast::cluster [%0], [%1, {%3, %4, %5}], [%2], %6;"
               ::"r"(dst), "l"(tm), "r"(bar), "r"(c0), "r"(c1), "r"(c2), "h"(mask) : "memory");
}
__device__ __forceinline__ void bulk_load(uint32_t dst, const void* src, uint32_t bytes, uint32_t bar) {
  asm volatile("cp.async.bulk.shared::cluster.global.mbarrier::complete_tx::bytes [%0], [%1], %2, [%3];"
               ::"r"(dst), "l"(src), "r"(bytes), "r"(bar) : "memory");
}
__device__ __forceinline__ void bulk_store(void* dst, uint32_t src, uint32_t bytes) {
  asm volatile("cp.async.bulk.global.shared::cta.bulk_group [%0], [%1], %2;" ::"l"(dst), "r"(src), "r"(bytes) : "memory");
}
__device__ __forceinline__ void bulk_prefetch(const void* src, uint32_t bytes) {
  asm volatile("cp.async.bulk.prefetch.L2.global [%0], %1;" ::"l"(src), "r"(bytes) : "memory");
}
__device__ __forceinline__ void bulk_commit() { asm volatile("cp.async.bulk.commit_group;" ::: "memory"); }
__device__ __forceinline__ void bulk_wait_read() { asm volatile("cp.async.bulk.wait_group.read 0;" ::: "memory"); }
__device__ __forceinline__ void bulk_wait_all() { asm volatile("cp.async.bulk.wait_group 0;" ::: "memory"); }
__device__ __forceinline__ void fence_async_smem() { asm volatile("fence.proxy.async.shared::cta;" ::: "memory"); }
__device__ __forceinline__ void wg_fence() { asm volatile("wgmma.fence.sync.aligned;" ::: "memory"); }
__device__ __forceinline__ void wg_commit() { asm volatile("wgmma.commit_group.sync.aligned;" ::: "memory"); }
template <int N> __device__ __forceinline__ void wg_wait() { asm volatile("wgmma.wait_group.sync.aligned %0;" ::"n"(N) : "memory"); }
__device__ __forceinline__ void bar_sync(int id, int n) { asm volatile("bar.sync %0, %1;" ::"r"(id), "r"(n) : "memory"); }
__device__ __forceinline__ void bar_arrive(int id, int n) { asm volatile("bar.arrive %0, %1;" ::"r"(id), "r"(n) : "memory"); }
__device__ __forceinline__ bool bar_red_or(int id, int n, bool v) {
  uint32_t r;
  asm volatile("{\n.reg .pred p, q;\nsetp.ne.u32 q, %3, 0;\nbar.red.or.pred p, %1, %2, q;\nselp.u32 %0, 1, 0, p;\n}\n"
               : "=r"(r) : "r"(id), "r"(n), "r"((uint32_t)v) : "memory");
  return r != 0;
}
__device__ __forceinline__ uint32_t movm(uint32_t a) { uint32_t d; asm volatile("movmatrix.sync.aligned.m8n8.trans.b16 %0, %1;" : "=r"(d) : "r"(a)); return d; }
__device__ __forceinline__ int f2ord(float x) { int i = __float_as_int(x); return i ^ ((i >> 31) & 0x7fffffff); }
__device__ __forceinline__ float ord2f(int i) { return __int_as_float(i ^ ((i >> 31) & 0x7fffffff)); }
__device__ __forceinline__ void cluster_sync() { asm volatile("barrier.cluster.arrive.aligned;\nbarrier.cluster.wait.aligned;" ::: "memory"); }
__device__ __forceinline__ float rcp_approx(float x) { float y; asm("rcp.approx.ftz.f32 %0, %1;" : "=f"(y) : "f"(x)); return y; }
__device__ __forceinline__ float ex2(float x) { float y; asm("ex2.approx.ftz.f32 %0, %1;" : "=f"(y) : "f"(x)); return y; }
__device__ __forceinline__ uint32_t pack_bf16(float lo, float hi) {
  uint32_t r; asm("cvt.rn.bf16x2.f32 %0, %1, %2;" : "=r"(r) : "f"(hi), "f"(lo)); return r;
}
__device__ __forceinline__ uint32_t hadd2(uint32_t a, uint32_t b) { uint32_t r; asm("add.rn.bf16x2 %0, %1, %2;" : "=r"(r) : "r"(a), "r"(b)); return r; }
__device__ __forceinline__ uint32_t umax2(uint32_t a, uint32_t b) { uint32_t r; asm("max.u16x2 %0, %1, %2;" : "=r"(r) : "r"(a), "r"(b)); return r; }
__device__ __forceinline__ uint32_t umin2(uint32_t a, uint32_t b) { uint32_t r; asm("min.u16x2 %0, %1, %2;" : "=r"(r) : "r"(a), "r"(b)); return r; }
__device__ __forceinline__ void stsm4(uint32_t addr, uint32_t a, uint32_t b, uint32_t c, uint32_t d) {
  asm volatile("stmatrix.sync.aligned.m8n8.x4.shared.b16 [%0], {%1,%2,%3,%4};" ::"r"(addr), "r"(a), "r"(b), "r"(c), "r"(d) : "memory");
}
__device__ __forceinline__ void stsm4t(uint32_t addr, uint32_t a, uint32_t b, uint32_t c, uint32_t d) {
  asm volatile("stmatrix.sync.aligned.m8n8.x4.trans.shared.b16 [%0], {%1,%2,%3,%4};" ::"r"(addr), "r"(a), "r"(b), "r"(c), "r"(d) : "memory");
}
__device__ __forceinline__ void sts128(uint32_t addr, uint32_t a, uint32_t b, uint32_t c, uint32_t d) {
  asm volatile("st.shared.v4.b32 [%0], {%1,%2,%3,%4};" ::"r"(addr), "r"(a), "r"(b), "r"(c), "r"(d) : "memory");
}
__device__ __forceinline__ void lds128(uint32_t addr, uint32_t& a, uint32_t& b, uint32_t& c, uint32_t& d) {
  asm volatile("ld.shared.v4.b32 {%0,%1,%2,%3}, [%4];" : "=r"(a), "=r"(b), "=r"(c), "=r"(d) : "r"(addr) : "memory");
}
__device__ __forceinline__ void sts64f(uint32_t addr, float a, float b) {
  asm volatile("st.shared.v2.f32 [%0], {%1,%2};" ::"r"(addr), "f"(a), "f"(b) : "memory");
}
__device__ __forceinline__ void lds64f(uint32_t addr, float& a, float& b) {
  asm volatile("ld.shared.v2.f32 {%0,%1}, [%2];" : "=f"(a), "=f"(b) : "r"(addr) : "memory");
}
constexpr uint64_t desc_hi(uint32_t lbo, uint32_t sbo, int swz) {
  return ((uint64_t)(lbo >> 4) << 16) | ((uint64_t)(sbo >> 4) << 32) | ((uint64_t)swz << 62);
}
__device__ __forceinline__ uint64_t mkdesc(uint32_t addr, uint64_t hi) { return hi | (uint64_t)((addr & 0x3FFFF) >> 4); }

constexpr uint64_t D_A64 = desc_hi(16, 512, 2);
constexpr uint64_t D_W = desc_hi(2048, 1024, 1);
constexpr uint64_t D_K = desc_hi(16, 1024, 1);
constexpr uint64_t D_V = desc_hi(16384, 1024, 1);
constexpr uint64_t D_N64 = desc_hi(16, 512, 2);
constexpr uint64_t D_O = desc_hi(2048, 128, 0);

__device__ __forceinline__ uint32_t op_ssz(uint32_t wm) { return wm == 0 ? 28672 : (wm == 1 ? 20480 : 16384); }
__device__ __forceinline__ uint32_t op_nsl(uint32_t wm) { return wm == 0 ? ONS0 : (wm == 1 ? ONS1 : ONS2); }

struct Ring {
  uint32_t slot, phase;
  __device__ __forceinline__ void next() { if (++slot == NSLOT) { slot = 0; phase ^= 1; } }
};

template <int N> __device__ __forceinline__ void pin(float (&a)[N]) {
#pragma unroll
  for (int i = 0; i < N; i++) asm volatile("" : "+f"(a[i]) :: "memory");
}
template <bool V> struct BoolC { static constexpr bool value = V; };

struct Params {
  CUtensorMap tm_x, tm_xl, tm_wq, tm_wo, tm_wo3, tm_wo2, tm_k, tm_v, tm_o, tm_out;
};

__device__ __forceinline__ void arrive_cluster_addr(uint32_t addr) {
  asm volatile("mbarrier.arrive.shared::cluster.b64 _, [%0];" ::"r"(addr) : "memory");
}
__device__ __forceinline__ uint32_t mapa(uint32_t addr, uint32_t cta) {
  uint32_t r; asm("mapa.shared::cluster.u32 %0, %1, %2;" : "=r"(r) : "r"(addr), "r"(cta)); return r;
}
__device__ __forceinline__ uint32_t lane_id() { uint32_t l; asm volatile("mov.u32 %0, %%laneid;" : "=r"(l)); return l; }
__device__ __forceinline__ bool elect_one() {
  uint32_t r;
  asm volatile("{\n.reg .pred p;\nelect.sync _|p, 0xffffffff;\nselp.u32 %0, 1, 0, p;\n}\n" : "=r"(r));
  return r != 0;
}
__device__ __forceinline__ void elect_arrive_cluster2(uint32_t a0, uint32_t a1) {
  asm volatile("{\n.reg .pred p;\nelect.sync _|p, 0xffffffff;\n"
               "@p mbarrier.arrive.shared::cluster.b64 _, [%0];\n@p mbarrier.arrive.shared::cluster.b64 _, [%1];\n}\n"
               ::"r"(a0), "r"(a1) : "memory");
}
__device__ __forceinline__ void elect_arrive_cluster2_if(uint32_t a0, uint32_t a1, bool c) {
  asm volatile("{\n.reg .pred p, q;\nelect.sync _|p, 0xffffffff;\nsetp.ne.and.u32 q, %2, 0, p;\n"
               "@q mbarrier.arrive.shared::cluster.b64 _, [%0];\n@q mbarrier.arrive.shared::cluster.b64 _, [%1];\n}\n"
               ::"r"(a0), "r"(a1), "r"((uint32_t)c) : "memory");
}
__device__ __forceinline__ bool mbar_try(uint32_t bar, uint32_t parity) {
  uint32_t r;
  asm volatile("{\n.reg .pred p;\nmbarrier.test_wait.parity.shared::cta.b64 p, [%1], %2;\nselp.u32 %0, 1, 0, p;\n}\n"
               : "=r"(r) : "r"(bar), "r"(parity) : "memory");
  return r != 0;
}
__device__ __forceinline__ void elect_arrive(uint32_t bar) {
  asm volatile("{\n.reg .pred p;\nelect.sync _|p, 0xffffffff;\n@p mbarrier.arrive.shared::cta.b64 _, [%0];\n}\n" ::"r"(bar) : "memory");
}
constexpr int OEMPTY = 512 + 128 - 64, XFREE = 216 - 64;
#define release_slot(be, slot, lane) do { if (signaller) elect_arrive_cluster2(empty0 + (slot) * 8, empty1 + (slot) * 8); } while (0)

__device__ __forceinline__ void arrive_cluster_addr2(uint32_t addr) {
  asm volatile("mbarrier.arrive.shared::cluster.b64 _, [%0], 2;" ::"r"(addr) : "memory");
}

__device__ __forceinline__ void arrive_cluster_addr3(uint32_t addr) {
  asm volatile("mbarrier.arrive.shared::cluster.b64 _, [%0], 3;" ::"r"(addr) : "memory");
}

#define JOB(q) c_all[(q) & 511]
#define JRING(q) Ring{(((q) >> 16) & 15) % NSLOT, (((q) >> 16) & 15) / NSLOT}
#define JSTART(q) (((((JOB(q).x >> 27) & 3) == 0 ? 0x04320u : (((JOB(q).x >> 27) & 3) == 1 ? 0x75420u : 0x86420u)) >> (((((q) >> 16) & 15) % NSLOT) * 4)) & 15)
#define ONEXT(slot, st0, n5, nsl) { if (++slot == (n5)) slot = 0; slot = slot == (st0) ? (n5) : (slot == (nsl) ? (st0) : slot); }
#define FREE_X(xs)                                                                                                   \
  {                                                                                                                  \
    if ((nx & 3) == 2) { arrive_cluster_addr(empty0 + XFREE); arrive_cluster_addr(empty1 + XFREE); }                 \
    else if ((nx & (3 | J_ATO)) == 1) { arrive_cluster_addr3(empty0 + (xs) * 8); arrive_cluster_addr3(empty1 + (xs) * 8); } \
  }

__global__ void __cluster_dims__(2, 1, 1) __launch_bounds__(512, 1)
fused_kernel(const uint8_t* __restrict__ xp, const uint8_t* __restrict__ wqp, const __nv_bfloat16* __restrict__ kc,
             const __nv_bfloat16* __restrict__ vc, __nv_bfloat16* __restrict__ out, const __grid_constant__ Params prm) {
  extern __shared__ __align__(1024) uint8_t smem_raw[];
  const uint32_t sb = smem_u32(smem_raw);
  const uint32_t bar_full = sb + OFF_BAR, bar_empty = sb + OFF_BAR + 64;
  const uint32_t bar_stm = sb + OFF_BAR + 128, bar_stl = sb + OFF_BAR + 136;
  const uint32_t bar_drm = sb + OFF_BAR + 144, bar_drl = sb + OFF_BAR + 152;
  const uint32_t epoch_addr = sb + OFF_BAR + 160;
  const uint32_t bar_go = sb + OFF_BAR + 192, bar_xfree = sb + OFF_BAR + 216, bar_q = sb + OFF_BAR + 224;
  const uint32_t bar_ofull = sb + OFF_BAR + 512;
  const uint32_t job_addr = sb + OFF_BAR + 256;
  const uint32_t rdy_addr = sb + OFF_BAR + 168;
  const int tid = threadIdx.x;
  const int warp = __shfl_sync(0xffffffffu, tid >> 5, 0);
  const int wg = warp >> 2;
  uint32_t rank;
  asm volatile("mov.u32 %0, %%cluster_ctarank;" : "=r"(rank));
  const int pair = blockIdx.x >> 1;
  const uint32_t empty0 = mapa(bar_empty, 0), empty1 = mapa(bar_empty, 1);
  const bool signaller = (warp & 3) == wg;
  const uint32_t sb4 = (sb & 0x3FFFF) >> 4;
#define DESC(hi, lo) (((hi) & ~0xffffffffull) | (uint32_t)(lo))

#define START_WAIT() asm volatile("barrier.cluster.wait.aligned;" ::: "memory")
#define QP_LOAD(dst, fb, s)                                                                                          \
  mbar_expect_tx(fb, A_TILE + 16384);                                                                                \
  tma_2d(dst, &prm.tm_x, (s) * 32, b * SQ, fb);                                                                      \
  tma_2d_mc((dst) + 8192 + rank * 2048, &prm.tm_xl, (s) * 32, b * SQ + 128, fb, 3);                                  \
  tma_3d_mc((dst) + A_TILE + rank * 8192, &prm.tm_wq, 0, (s) * 32 + rank * 16, hp * 4, fb, 3);
  uint32_t jx0, jy0, jz0, jw0;
  asm volatile("{\n.reg .pred p;\nsetp.eq.u32 p, %5, 8;\nmov.u32 %0, 0;\nmov.u32 %1, 0;\nmov.u32 %2, 0;\nmov.u32 %3, 0;\n@p ld.const.v4.u32 {%0, %1, %2, %3}, [%4];\n}\n"
               : "=r"(jx0), "=r"(jy0), "=r"(jz0), "=r"(jw0) : "l"(__cvta_generic_to_constant(&c_all[pair + threadIdx.y])), "r"(tid >> 5));
  if (warp != 8) {
    {
      const uint32_t g = blockIdx.x * 64 + (tid & 63), xr = g >> 1;
      const uint8_t* a = tid < 128 ? wqp + g * 256 : xp + (xr + (xr < NB0 * SQ ? 0 : (16 - NB0) * SQ)) * (D_ * 2) + (g & 1) * 256;
      if (tid < 128 ? tid >= 64 && g < PRE_ROWS * 32 && (g & 31) < 2 * NH0 : tid < 192 && xr < 2 * NB0 * SQ)
        asm volatile("cp.async.ca.shared.global.L2::256B [%0], [%1], 4;" ::"r"(sb + OFF_BAR + 384), "l"(a) : "memory");
    }
    if (warp == 13 && (blockIdx.x & TLBM) < 8)
      asm volatile("cp.async.ca.shared.global [%0], [%1], 4;" ::"r"(sb + OFF_BAR + 384),
                   "l"((const uint8_t*)((blockIdx.x & 4) ? vc : kc) + (size_t)((blockIdx.x & 3) * 32 + (tid & 31)) * 1048576) : "memory");
    if (elect_one()) {
      const int w = warp - (warp >> 3);
      if (w < NTMPF) asm volatile("prefetch.tensormap [%0];" ::"l"(&prm.tm_x + w) : "memory");
      if (w < 13) { mbar_init(bar_ofull + w * 8, 1); mbar_init(bar_ofull + 128 + w * 8, 4); }
      if (w < NSLOT + 2) mbar_init(bar_full + w * 8, 1);
      mbar_init(w < NSLOT + 2 ? bar_empty + w * 8 : bar_stm + ((0xdcb8a32100000000ull >> (w * 4)) & 15) * 8,
                (0x1141411486666666ull >> (w * 4)) & 15);
      if (w == 13) {
        if ((sb & 1023) || (sb & 0x3FFFF) >= 4096) asm volatile("trap;");
        mbar_init(bar_q + 8, 1);
        sts128(epoch_addr, 0, 0, 0, 0);
        sts128(sb + OFF_BAR + 240, 0, 0, 0, 0);
        sts128(job_addr, pair | 1 << 24, 0, 0, 0);
        for (int i = 1; i < 6; i++) sts128(job_addr + 16 * i, 0, 0, 0, 0);
        asm volatile("fence.acq_rel.cta;" ::: "memory");
      }
      asm volatile("fence.mbarrier_init.release.cluster;" ::: "memory");
    }
    __syncwarp();
  }
  asm volatile("barrier.cluster.arrive.relaxed.aligned;" ::: "memory");

  if (wg == 3) {
    asm volatile("setmaxnreg.dec.sync.aligned.u32 24;");
    const int lane = lane_id();
#define Q_READY(jy)                                                                                                  \
  flag_wait<true>(&g_oflag[((jy) & 0xffff) + (lane & 1) * QFLAG], epoch_get(epoch_addr) * 2);                        \
  __syncwarp();                                                                                                      \
  fence_async_all();
#define Q_PTR(jy, rk) (g_q + (((jy) >> 16) * 2 + (rk)) * Q_BYTES)
    if (warp == 12) {
      START_WAIT();
      jx0 = c_all[pair].x;
      Ring r{0, (jx0 & J_DUMMY) ? 1u : 0u};
      uint64_t pol;
      asm volatile("createpolicy.fractional.L2::evict_first.b64 %0, 1.0;" : "=l"(pol));
      uint32_t need = 0;
      uint32_t oslot = 0, oleft = 0, oph = 0;
      uint32_t xph = (jx0 & J_DUMMY) ? 0 : 1;
      for (int ji = 0; ji < NJOB; ji++) {
        const uint32_t jq = job_get(job_addr, ji), jx = JOB(jq).x;
        if ((jx & 3) == 0) break;
        if ((jx & 3) == 1) {
          const uint32_t jw = JOB(jq).w, t0 = clock();
          const int row0 = ((((jx >> 4) & 15) + rank * 16 + (jx & 8) * 4) * H_ + ((jx >> 8) & 15) * 2) * SK;
          if (jx & J_ATO) {
            count_wait(sb + OFF_BAR + 244, ji);
            fence_async_all();
            mbar_wait(bar_empty + r.slot * 8, r.phase);
            if (elect_one()) {
              mbar_expect_tx(bar_full + r.slot * 8, SLOT);
              bulk_load(sb + r.slot * SLOT, Q_PTR(JOB(jq).y, rank) + 32768, SLOT, bar_full + r.slot * 8);
            }
            r.next();
          }
          if ((jx & J_QO) && elect_one()) mbar_arrive(bar_go);
          for (int s2 = (jx >> 20) & 63; s2 < 76 - (jx & J_QO) * 4; s2++) {
            const uint32_t ju = s2 < 40 ? (s2 < 20 ? JOB(jq).z : JOB(jq).y) : jx;
            const int s = s2 < 40 ? (s2 < 20 ? s2 : s2 - 20) : s2 - 40;
            const bool xs = s < 20 && ((XST >> s) & 1) && !(ju & J_PRE);
            const uint32_t sl = xs ? NSLOT + ((s ^ (s >> 3) ^ 1) & 1) : r.slot;
            const uint32_t dst = sb + sl * SLOT, fb = bar_full + sl * 8;
            mbar_wait(bar_empty + sl * 8, xs ? xph ^ (s >> 3) : r.phase);
            if (s == 13) xph ^= 1;
            if (s < 20) {
              const int b = ((ju >> 4) & 15) + rank * 16 + (ju & 8) * 4, hp = (ju >> 8) & 15;
              if (elect_one()) {
                QP_LOAD(dst, fb, s)
              }
            } else {
              const int t = s - 20;
              if (jw != 0) {
                const uint32_t due = (jw & 0xffff) + t * (jw >> 16);
                for (int it = 0; it < 100000 && (uint32_t)clock() - t0 < due; it++) asm volatile("nanosleep.u32 100;");
              }
              if (KV_DEPTH < NSLOT) {
                const uint32_t ws = r.slot >= KV_DEPTH ? r.slot - KV_DEPTH : r.slot + NSLOT - KV_DEPTH;
                mbar_wait(bar_full + ws * 8, r.slot >= KV_DEPTH ? r.phase ^ 1 : r.phase);
              }
              if (elect_one()) {
                mbar_expect_tx(fb, SLOT);
                tma_3d_hint(dst, (t & 1) ? &prm.tm_v : &prm.tm_k, 0, row0 + ((t >> 1) ^ (rank * 4)) * 128, 0, fb, pol);
                if (t == PF_GO) mbar_arrive(bar_go);
              }
            }
            if (!xs) r.next();
          }
        } else {
          const int c0 = OALR(((jx >> 4) & 31) * 2 + rank) * 256, cb = (JOB(jq).y >> 16) & 15;
          const int nh = (jx >> 19) & 63;
          const uint32_t wm = (jx >> 27) & 3;
          const uint32_t nsl = op_nsl(wm), ssz = op_ssz(wm), woff = 8192 + rank * ((ssz - 8192) >> 1);
          const uint32_t jw = JOB(jq).w;
          const CUtensorMap* tmw = &prm.tm_wo + wm;
          const uint32_t st0 = JSTART(jq), n5 = (0xa85 >> (wm * 4)) & 15;
          if (jw & 7) { oslot = st0; oleft = nsl; oph = 2; }
          if (jw & 1) mbar_wait(bar_xfree, 0);
          uint32_t dst = sb + oslot * ssz, fb = bar_ofull + oslot * 8;
#pragma unroll 1
          for (int q = 0; q < nh; q++) {
            const int h = byte_get(job_addr + 32 + need++) - 1;
            asm volatile("fence.proxy.async.global;" ::: "memory");
#pragma unroll
            for (int k = 0; k < 4; k++) {
              if (oph == 2) {
                const uint32_t u0 = (dst - sb) >> 15, u1 = (dst - sb + ssz - 1) >> 15;
                if (u0 < NSLOT) mbar_wait(bar_empty + u0 * 8, u0 >= r.slot ? r.phase : r.phase ^ 1);
                mbar_wait(u1 < NSLOT ? bar_empty + u1 * 8 : bar_xfree, u1 < NSLOT ? (u1 >= r.slot ? r.phase : r.phase ^ 1) : 0);
              } else {
                mbar_wait(fb + 128, oph);
              }
              if (elect_one()) {
                if (ji == 2 && q < 2) PROF_H(4 + q * 4 + k);
                mbar_expect_tx(fb, ssz);
                tma_2d_hint(dst, &prm.tm_o, c0, OALH(h) * 16 + k * 4, fb, pol);
                tma_3d_mc(dst + woff, tmw, 0, h * 128 + k * 32 + rank * 16, cb, fb, 3);
              }
              ONEXT(oslot, st0, n5, nsl)
              dst = sb + oslot * ssz; fb = bar_ofull + oslot * 8;
              if (--oleft == 0) { oleft = nsl; oph = oph == 0; }
            }
            asm volatile("st.volatile.shared.u32 [%0], %1;" ::"r"(rdy_addr + 4), "r"(need * 4) : "memory");
          }
          if (jx & J_LAST) break;
        }
      }
    } else if (warp == 13) {
      START_WAIT();
      if (lane == 0 && c_init[pair].y != 0)
        asm volatile("st.volatile.shared.u32 [%0], %1;\nst.volatile.shared.u32 [%0 + 4], %2;" ::"r"(job_addr + 4), "r"(c_init[pair].y), "r"(c_init[pair].z) : "memory");
      uint32_t ph = 0;
      int j0 = 0;
      if (c_all[pair].x & J_PRE) {
        j0 = (c_all[pair].x & J_QO) != 0;
#pragma unroll 1
        for (int ps = 0, np = j0 + ((c_all[pair].x & J_Q3) != 0); ps <= np; ps++) {
          const int nx = j0 && ps == np ? 2 : 1;
          mbar_wait(bar_stm, ph); ph ^= 1;
          if (lane == 0) {
#pragma unroll 1
            for (int i = 0; i < 16; i++) {
              bulk_store(Q_PTR(c_all[pair].y, rank + 2 * ps) + i * 4096, sb + OFF_STASH + i * 4096, 4096);
              if (nx == 1) asm volatile("nanosleep.u32 %0;" ::"n"(QPACE));
            }
            bulk_commit();
            bulk_wait_read();
            if (nx == 1) FREE_X(NSLOT + 1)
            FREE_X(NSLOT)
          }
          __syncwarp();
        }
        bulk_wait_all();
        __syncwarp();
        if (lane == 0 && j0) asm volatile("red." FLAGSEM ".gpu.global.add.u32 [%0], 1;" ::"l"(&g_oflag[B_ * H_ + pair + rank * QFLAG]) : "memory");
      }
      for (int ji = j0; ji < NJOB; ji++) {
        const uint32_t jq = job_get(job_addr, ji), jx = JOB(jq).x;
        if ((jx & 3) == 0) break;
        if ((jx & 3) == 1) {
          const int b = ((jx >> 4) & 15) + rank * 16, hp = (jx >> 8) & 15;
          for (int hh = 0; hh < 2; hh++) {
            const uint32_t nq = hh ? job_get(job_addr, ji + 1) : 0, nx = hh ? JOB(nq).x : 0;
            if ((nx & (3 | J_ATO)) == (1 | J_ATO)) {
              count_wait(sb + OFF_BAR + 244, ji + 1);
              fence_async_all();
            }
            mbar_wait(bar_stm, ph); ph ^= 1;
            PROF_M(0);
            if (lane < 16 && !(jx & 8))
              bulk_store((uint8_t*)g_o + (size_t)(OALH(hp * 2 + (hh ^ rank)) * 16 + lane) * O_PLANE + OAL(b) * SQ * 16, sb + OFF_STASH + lane * 2048, 2048);
            bulk_commit();
            const bool claim = hh == 0 && rank == 0 && (jx & J_CLAIM) && lane == 0;
            uint32_t n = 0;
            if (claim) n = atomicAdd(&g_queue, 1u);
            bulk_wait_read();
            __syncwarp();
            PROF_M(1);
            if (lane == 0) {
              if ((nx & (3 | J_ATO)) == (1 | J_ATO)) {
                mbar_expect_tx(bar_drm, 32768);
                bulk_load(sb + OFF_STASH, Q_PTR(JOB(nq).y, rank), 32768, bar_drm);
              } else {
                mbar_arrive(bar_drm);
              }
              if (hh == 1) FREE_X(NSLOT)
            }
            bulk_wait_all();
            __syncwarp();
            if (claim) {
              n -= (epoch_get(epoch_addr) - 1) * NCLAIM;
              uint32_t pos = ((jq >> 16) & 15) + ((jx >> 16) & 15);
              if (pos >= 2 * NSLOT) pos -= 2 * NSLOT;
              const uint32_t wd = (QBASE + min(n, NQUEUE)) | pos << 16 | (ji + 2) << 24, ad = job_addr + ((ji + 1) & 7) * 4;
              asm volatile("st.volatile.shared::cluster.u32 [%0], %1;" ::"r"(mapa(ad, 1)), "r"(wd) : "memory");
              asm volatile("st.volatile.shared.u32 [%0], %1;" ::"r"(ad), "r"(wd) : "memory");
            }
            PROF_M(2);
            if (lane == 0 && !(jx & 8)) asm volatile("red." FLAGSEM ".gpu.global.add.u32 [%0], 1;" ::"l"(&g_oflag[b * H_ + hp * 2 + (hh ^ rank)]) : "memory");
            PROF_M(3);
          }
        } else break;
      }
      bulk_wait_all();
    } else if (warp == 14) {
      START_WAIT();
      if (lane == 0) {
        const unsigned long long t = atomicAdd(&g_ticket, 1ull);
        asm volatile("st.volatile.shared.v2.u32 [%0], {%1, %2};" ::"r"(epoch_addr), "r"((uint32_t)(t / (2 * NPAIR)) + 1u), "r"(1) : "memory");
      }
      __syncwarp();
      uint32_t ph = 0, base = 0;
      for (int ji = (c_all[pair].x & J_QO) != 0; ji < NJOB; ji++) {
        const uint32_t jq = job_get(job_addr, ji), jx = JOB(jq).x;
        if ((jx & 3) == 0) break;
        if ((jx & 3) == 1) {
          const int b = ((jx >> 4) & 15) + rank * 16, hp = (jx >> 8) & 15;
          for (int hh = 0; hh < 2; hh++) {
            const uint32_t nq = hh ? job_get(job_addr, ji + 1) : 0, nx = hh ? JOB(nq).x : 0;
            if ((nx & (3 | J_ATO)) == (1 | J_ATO)) {
              count_wait(sb + OFF_BAR + 244, ji + 1);
              fence_async_all();
              if (lane == 0) bulk_load(sb + OFF_QL, Q_PTR(JOB(nq).y, rank) + 65536, 8192, bar_q);
            }
            mbar_wait(bar_stl + hh * 72, ph);
            if (lane < 16 && !(jx & J_DUMMY))
              bulk_store((uint8_t*)g_o + (size_t)(OALH(hp * 2 + (hh ^ rank)) * 16 + lane) * O_PLANE + (OAL(b) * SQ + 128) * 16,
                         sb + OFF_QL + hh * 8192 + lane * 512, 512);
            bulk_commit();
            if (hh == 1) {
              bulk_wait_read();
              __syncwarp();
              if (lane == 0) {
                if ((nx & (3 | J_ATO)) == (1 | J_ATO)) {
                  mbar_expect_tx(bar_drl, 8192);
                  bulk_load(sb + OFF_QL + 8192, Q_PTR(JOB(nq).y, rank) + 65536 + 8192, 8192, bar_drl);
                } else {
                  mbar_arrive(bar_drl);
                }
                FREE_X(NSLOT + 1)
              }
            }
            bulk_wait_all();
            __syncwarp();
            if (lane == 0 && !(jx & J_DUMMY))
              asm volatile("red." FLAGSEM ".gpu.global.add.u32 [%0], 1;" ::"l"(&g_oflag[b * H_ + hp * 2 + (hh ^ rank)]) : "memory");
          }
          ph ^= 1;
        } else {
          const int ns = (jx >> 17) & 255;
          if (DISCARD && (jx >> 25) == 0) {
            const int rt = ((jx >> 4) & 31) * 2 + rank;
            const uint32_t ep = epoch_get(epoch_addr);
            const int lim = (jx & J_LAST) ? ns - ONS0 : ns;
            for (int q = 0; 4 * q + 4 <= lim; q++) {
              count_wait(rdy_addr + 4, base + 4 * q + 4 + ONS0);
              const int h = byte_get(job_addr + 32 + (base >> 2) + q) - 1;
              uint32_t old = 0;
              if (lane == 0) asm volatile("atom.exch.acq_rel.gpu.global.b32 %0, [%1], %2;" : "=r"(old) : "l"(&g_oread[rt * H_ + h]), "r"(ep) : "memory");
              if (__shfl_sync(0xffffffffu, old, 0) == ep) {
                const uint8_t* a = (const uint8_t*)g_o + (size_t)(h * 16 + (lane >> 1)) * O_PLANE + rt * 2048 + (lane & 1) * 1024;
#pragma unroll
                for (int i = 0; i < 8; i++) asm volatile("discard.global.L2 [%0], 128;" ::"l"(a + i * 128) : "memory");
              }
            }
          }
          base += ns;
          if (jx & J_LAST) break;
        }
      }
    } else {
      const uint32_t dummy = sb + OFF_BAR + 384 + lane * 4;
      uint32_t gp = 0, nrdy = 0;
      for (int ji = 0; ji < NJOB; ji++) {
        if (ji == 1) START_WAIT();
        const uint32_t jq = ji ? job_get<250>(job_addr, ji) : pair, jx = JOB(jq).x;
        if ((jx & (3 | J_ATO)) == (1 | J_ATO)) {
          Q_READY(JOB(jq).y)
          if (lane == 0) asm volatile("st.release.cta.shared.u32 [%0], %1;" ::"r"(sb + OFF_BAR + 244), "r"(ji) : "memory");
        }
        if (nrdy == 0 && ji != 0) { mbar_wait_soft(bar_go, gp); gp ^= 1; }
        if ((jx & 3) == 0) break;
        if ((jx & 3) == 1) {
          const int row0 = ((((jx >> 4) & 15) + rank * 16) * H_ + ((jx >> 8) & 15) * 2) * SK;
          const uint32_t pfm = (jx & (J_QO | J_Q3)) ? 0 : JOB(jq).z;
          if (jx & J_PRE) {
            const uint32_t t0 = clock();
            asm volatile("nanosleep.u32 %0;" ::"n"(PRE2NS));
#pragma unroll 1
            for (int s = 0; s < PRE2; s++) {
              const uint8_t* a = s < 20 ? wqp + (s * 32 + rank * 16 + (lane >> 1)) * 8192 + ((jx >> 8) & 15) * 512 + (lane & 1) * 256
                                        : xp + (((jx >> 4) & 15) + rank * 16) * (SQ * D_ * 2) + (s - 20) * 8192 + lane * 256;
              asm volatile("cp.async.ca.shared.global.L2::256B [%0], [%1], 4;" ::"r"(dummy), "l"(a) : "memory");
              asm volatile("cp.async.commit_group;" ::: "memory");
              asm volatile("cp.async.wait_group %0;" ::"n"(PRE2W) : "memory");
            }
            for (int it = 0; it < 100000 && (uint32_t)clock() - t0 < (JOB(jq).w & 0xffff); it++) asm volatile("nanosleep.u32 100;");
          }
#pragma unroll 1
          for (int t = 0; t < 16; t++) {
            if (!((pfm >> t) & 1)) continue;
            const uint8_t* src = (const uint8_t*)((t & 1) ? vc : kc) + (size_t)row0 * 256 + ((t >> 1) ^ (rank * 4)) * SLOT + lane * 256;
#pragma unroll
            for (int k = 0; k < 4; k++) {
              asm volatile("cp.async.ca.shared.global.L2::256B [%0], [%1], 4;" ::"r"(dummy), "l"(src + k * 8192) : "memory");
              if ((pfm >> (16 + k)) & 1) continue;
              asm volatile("cp.async.commit_group;" ::: "memory");
              asm volatile("cp.async.wait_group %0;" ::"n"(PF_WIN - 1) : "memory");
            }
          }
        } else {
          if (rank != 0) break;
          const int r0 = ((jx >> 4) & 31) * 256, nh = (jx >> 19) & 63;
          const uint32_t target = epoch_get(epoch_addr) * 2, h = c_order[JOB(jq).w >> 12][lane];
          const unsigned int* f = &g_oflag[r0 / 160 * H_ + h];
          const int b2 = ((r0 + 255) / 160 - r0 / 160) * H_;
          bool todo = lane < nh;
          for (uint32_t it = 0, left = nh; left != 0; it++) {
            int v0 = 0, v1 = 0, v2 = 0;
            if (todo) {
              asm volatile("ld.relaxed.gpu.global.s32 %0, [%1];" : "=r"(v0) : "l"(f) : "memory");
              asm volatile("ld.relaxed.gpu.global.s32 %0, [%1];" : "=r"(v1) : "l"(f + H_) : "memory");
              asm volatile("ld.acquire.gpu.global.s32 %0, [%1];" : "=r"(v2) : "l"(f + b2) : "memory");
            }
            const bool ok = todo && ((v0 - (int)target) | (v1 - (int)target) | (v2 - (int)target)) >= 0;
            const uint32_t m = __ballot_sync(0xffffffffu, ok);
            if (ok) {
              const uint32_t ad = job_addr + 32 + nrdy + __popc(m & ((1u << lane) - 1));
              asm volatile("st.volatile.shared::cluster.u8 [%0], %1;" ::"r"(mapa(ad, 1)), "r"(h + 1) : "memory");
              asm volatile("st.volatile.shared.u8 [%0], %1;" ::"r"(ad), "r"(h + 1) : "memory");
              todo = false;
            }
            nrdy += __popc(m); left -= __popc(m);
            if (left > 8) asm volatile("nanosleep.u32 64;");
            asm volatile("{\n.reg .pred p;\nsetp.gt.u32 p, %0, 4000000;\n@p trap;\n}\n" ::"r"(it));
          }
          if (jx & J_LAST) break;
        }
      }
      asm volatile("cp.async.wait_group 0;" ::: "memory");
    }
    __syncwarp();
    cluster_sync();
  } else if (wg < 2) {
    asm volatile("setmaxnreg.inc.sync.aligned.u32 192;");
    START_WAIT();
    uint32_t stash;
    { const int lane = lane_id(); stash = sb + OFF_STASH + (lane >> 4) * 2048 + warp * 256 + (lane & 15) * 16; }
    int jn = 0;
    {
#pragma unroll 1
      for (; jn < NJOB; jn++) {
        const int ji = __shfl_sync(0xffffffffu, jn, 0);
        const uint32_t jq = job_get(job_addr, ji);
        if ((JOB(jq).x & 3) != 1) break;
        Ring r = JRING(jq);
        float s[64], o[64];
        uint32_t qf[32];
        PROF_T(1);
        const uint32_t qa = (uint32_t)D_A64 + sb4 + wg * 256;
        const uint32_t qb = (uint32_t)D_W + sb4 + A_TILE / 16 + rank * 256, qc = (uint32_t)D_W + sb4 + A_TILE / 16 + (rank ^ 1) * 256;
#define QP_MMA(acc, qx, sl, acc0)                                                                                    \
  WgSS<128, 0, 1>::mma(acc, DESC(D_A64, qa + (sl) * (SLOT / 16)), DESC(D_W, (qx) + (sl) * (SLOT / 16)), acc0);       \
  WgSS<128, 0, 1>::mma(acc, DESC(D_A64, qa + (sl) * (SLOT / 16) + 2), DESC(D_W, (qx) + (sl) * (SLOT / 16) + 512), 1);
        uint32_t sa = 0, sc = 0;
#define STASH_Q()                                                                                                    \
  _Pragma("unroll") for (int i = 0; i < 8; i++)                                                                      \
    sts128(stash + i * 4096, pack_bf16(o[8 * i] * SCALE_LOG2, o[8 * i + 1] * SCALE_LOG2), pack_bf16(o[8 * i + 2] * SCALE_LOG2, o[8 * i + 3] * SCALE_LOG2), \
           pack_bf16(o[8 * i + 4] * SCALE_LOG2, o[8 * i + 5] * SCALE_LOG2), pack_bf16(o[8 * i + 6] * SCALE_LOG2, o[8 * i + 7] * SCALE_LOG2));
        uint32_t jf = JOB(jq).x & (J_PRE | J_ATO | J_QO | J_Q3), xm = XST;
        if (jf & J_ATO) {
          mbar_wait(bar_full + r.slot * 8, r.phase);
#pragma unroll
          for (int i = 0; i < 8; i++) lds128(stash - OFF_STASH + r.slot * SLOT + i * 4096, qf[4 * i], qf[4 * i + 1], qf[4 * i + 2], qf[4 * i + 3]);
#pragma unroll
          for (int i = 0; i < 64; i++) o[i] = 0.f;
          bar_sync(10 + wg, 128);
          release_slot(bar_empty, r.slot, lane);
          r.next();
        } else for (;;) {
          uint32_t prev = r.slot;
          mbar_wait(bar_full + r.slot * 8, r.phase);
          if (ji == 0) PROF_T(13);
          wg_fence();
          WgSS<128, 0, 1>::mma0(s, DESC(D_A64, qa + prev * (SLOT / 16)), DESC(D_W, qb + prev * (SLOT / 16)));
          WgSS<128, 0, 1>::mma0(o, DESC(D_A64, qa + prev * (SLOT / 16)), DESC(D_W, qc + prev * (SLOT / 16)));
          WgSS<128, 0, 1>::mma(s, DESC(D_A64, qa + prev * (SLOT / 16) + 2), DESC(D_W, qb + prev * (SLOT / 16) + 512), 1);
          WgSS<128, 0, 1>::mma(o, DESC(D_A64, qa + prev * (SLOT / 16) + 2), DESC(D_W, qc + prev * (SLOT / 16) + 512), 1);
          wg_commit();
          r.next();
#pragma unroll 1
          for (int st = (JOB(jq).x & J_DUMMY) ? 17 : 1; st < 18; st++) {
            const bool xs = (xm >> st) & 1;
            const uint32_t sl = xs ? NSLOT + ((st ^ (st >> 3) ^ 1) & 1) : r.slot;
            mbar_wait(bar_full + sl * 8, xs ? st >> 3 : r.phase);
            wg_fence();
            QP_MMA(s, qb, sl, 1)
            QP_MMA(o, qc, sl, 1)
            wg_commit();
            wg_wait<1>();
            elect_arrive_cluster2_if(empty0 + prev * 8, empty1 + prev * 8, signaller);
            prev = sl;
            if (!xs) r.next();
          }
          sa = r.slot;
          mbar_wait(bar_full + r.slot * 8, r.phase);
          r.next();
          sc = r.slot;
          mbar_wait(bar_full + r.slot * 8, r.phase);
          r.next();
          PROF_F(5);
          wg_fence();
          QP_MMA(s, qb, sa, 1) QP_MMA(s, qb, sc, 1)
          wg_commit();
          PROF_F(7);
          wg_wait<0>();
          pin(s);
          release_slot(bar_empty, prev, lane);
#pragma unroll
          for (int i = 0; i < 32; i++) qf[i] = pack_bf16(s[2 * i] * SCALE_LOG2, s[2 * i + 1] * SCALE_LOG2);
          if (!xm) mbar_wait(bar_empty + NSLOT * 8, !(jf & J_PRE) && (JOB(jq).x & J_Q3));
          if (!jf) break;
          wg_fence();
          QP_MMA(o, qc, sa, 1) QP_MMA(o, qc, sc, 1)
          wg_commit();
          PROF_T(15);
#pragma unroll
          for (int i = 0; i < 8; i++) sts128(stash + 32768 + i * 4096, qf[4 * i], qf[4 * i + 1], qf[4 * i + 2], qf[4 * i + 3]);
          wg_wait<0>();
          pin(o);
          release_slot(bar_empty, sa, lane);
          release_slot(bar_empty, sc, lane);
          STASH_Q()
          fence_async_smem();
          __syncwarp();
          elect_arrive(bar_stm);
          PROF_T(15);
          if (jf == J_QO) break;
          jf &= (jf & J_Q3) ? ~J_Q3 : J_QO; xm = 0;
        }
        if (jf == J_QO) continue;
        PROF_T(2);
#define STAGE_O()                                                                                                    \
  _Pragma("unroll") for (int i = 0; i < 8; i++)                                                                      \
    stsm4(stash + i * 4096, pack_bf16(o[8 * i] * r0, o[8 * i + 1] * r0), pack_bf16(o[8 * i + 2] * r1, o[8 * i + 3] * r1), \
          pack_bf16(o[8 * i + 4] * r0, o[8 * i + 5] * r0), pack_bf16(o[8 * i + 6] * r1, o[8 * i + 7] * r1));
#define ISSUE_S(sx, db)                                                                                              \
  wg_fence();                                                                                                        \
  WgRS<64, 0>::mma0(sx, qf[0], qf[1], qf[2], qf[3], (db));                                                           \
  _Pragma("unroll") for (int k = 1; k < 8; k++)                                                                      \
    WgRS<64, 0>::mma(sx, qf[4 * k], qf[4 * k + 1], qf[4 * k + 2], qf[4 * k + 3], (db) + (k >> 2) * 1024 + (k & 3) * 2, 1);
#define EXPS(p)                                                                                                      \
  _Pragma("unroll") for (int i = 0; i < 8; i++) {                                                                    \
    const float e0 = ex2(sx[4 * i]), e1 = ex2(sx[4 * i + 1]), e2 = ex2(sx[4 * i + 2]), e3 = ex2(sx[4 * i + 3]);      \
    if (i == 0) { u0 = l0 + e0; u2 = e1; u1 = l1 + e2; u3 = e3; } else { u0 += e0; u2 += e1; u1 += e2; u3 += e3; }   \
    p[2 * i] = pack_bf16(e0, e1);                                                                                    \
    p[2 * i + 1] = pack_bf16(e2, e3);                                                                                \
  }                                                                                                                  \
  u0 += u2; u1 += u3;
        float n0 = 0.f, n1 = 0.f, l0 = 0.f, l1 = 0.f;
        bool slow = false;
        float sx[32];
#define TOKEN_GET() bar_sync(5 + wg, 256)
#define TOKEN_PUT(last) bar_arrive((last) ? 6 - wg : 6 + wg, 256)
        {
          int k = 1;
          uint32_t pa[16], pb[16], prev, rel, dk_, dv_;
          float u0, u1, u2, u3, r0 = 0.f, r1 = 0.f;
          bool special, redo;
#define UNSAFE() (!(u0 + u1 <= SUM_HI) | (fminf(u0, u1) < SUM_LO))
#define ROW_SUMS()                                                                                                   \
  r0 = l0 + __shfl_xor_sync(0xffffffffu, l0, 1); r1 = l1 + __shfl_xor_sync(0xffffffffu, l1, 1);                      \
  r0 += __shfl_xor_sync(0xffffffffu, r0, 2); r1 += __shfl_xor_sync(0xffffffffu, r1, 2);                              \
  r0 = rcp_approx(r0); r1 = rcp_approx(r1);
#define ISSUE_PV(p, dv, acc)                                                                                         \
  _Pragma("unroll") for (int i = 0; i < 4; i++)                                                                      \
    WgRS<128, 1>::mma(o, p[4 * i], p[4 * i + 1], p[4 * i + 2], p[4 * i + 3], DESC(D_V, (dv) + i * 128), (acc) || i != 0); \
  wg_commit();
#define NEXT_Q()                                                        \
  _Pragma("unroll") for (int i = 0; i < 8; i++)                                                                      \
    asm volatile("{\n.reg .pred p;\nsetp.eq.u32 p, %5, 8;\n@p ld.shared.v4.b32 {%0,%1,%2,%3}, [%4];\n}\n"           \
                 : "+r"(qf[4 * i]), "+r"(qf[4 * i + 1]), "+r"(qf[4 * i + 2]), "+r"(qf[4 * i + 3]) : "r"(stash + i * 4096), "r"(k) : "memory");
#define TURN(pin_, pout, dk, dv, acc, EXTRA, cond, L_SPEC, EXTRA2)                                                           \
  {                                                                                                                  \
    PROF_F(4);                                                                                                       \
    TOKEN_GET();                                                                                                     \
    ISSUE_S(sx, DESC(D_K, dk_));                                                                                     \
    wg_commit();                                                                                                     \
    ISSUE_PV(pin_, dv_, acc)                                                                                         \
    TOKEN_PUT(false);                                                                                                \
    PROF_F(7);                                                                                                       \
  }                                                                                                                  \
  elect_arrive_cluster2_if(empty0 + rel * 8, empty1 + rel * 8, signaller & (k != 1));                                \
  k++;                                                                                                               \
  rel = prev;                                                                                                        \
  prev = r.slot;                                                                                                     \
  r.next();                                                                                                          \
  special = !mbar_try(bar_full + r.slot * 8, r.phase) | (cond);                                                      \
  dk_ = (uint32_t)D_K + sb4 + (dk); dv_ = (uint32_t)D_V + sb4 + (dv);                          \
  EXTRA                                                                                                              \
  if (slow) { wg_wait<0>(); goto L_SLOW; }                                                                           \
  wg_wait<1>();                                                                                                      \
  pin(sx);                                                                                                           \
  EXTRA2                                                                                                             \
  EXPS(pout)                                                                                                         \
  _Pragma("unroll") for (int i = 0; i < 16; i++) asm volatile("" : "+r"(pout[i]) :: "memory");                       \
  if (__any_sync(0xffffffffu, UNSAFE() | special)) { wg_wait<0>(); goto L_SPEC; }                                    \
  wg_wait<0>();                                                                                                      \
  l0 = u0; l1 = u1;
          mbar_wait(bar_full + r.slot * 8, r.phase);
          rel = 0;
          prev = r.slot;
          r.next();
          dk_ = (uint32_t)D_K + sb4 + prev * (SLOT / 16) + 512; dv_ = (uint32_t)D_V + sb4 + r.slot * (SLOT / 16);
          redo = false;
          PROF_F(3);
          TOKEN_GET();
          if (jf) {
            ISSUE_S(sx, DESC(D_K, dk_ - 512));
            wg_commit();
            TOKEN_PUT(true);
            wg_wait<0>();
            pin(sx);
            goto L_EXP;
          }
          ISSUE_S(sx, DESC(D_K, dk_ - 512));
          wg_commit();
          TOKEN_PUT(true);
          QP_MMA(o, qc, sa, 1) QP_MMA(o, qc, sc, 1)
          wg_commit();
          PROF_F(6);
          wg_wait<1>();
          pin(sx);
          EXPS(pa)
#pragma unroll
          for (int i = 0; i < 16; i++) asm volatile("" : "+r"(pa[i]) :: "memory");
          wg_wait<0>();
          pin(o);
          release_slot(bar_empty, sa, lane);
          release_slot(bar_empty, sc, lane);
          STASH_Q()
          if (__any_sync(0xffffffffu, UNSAFE())) goto L_RARE;
          goto L_A2;
        L_ODD:
          TURN(pa, pb, r.slot * (SLOT / 16), prev * (SLOT / 16) + 512, (k & 7) != 1,
               if ((k | 2) == 10) { if (k == 8) mbar_wait(bar_drm, 1); else { fence_async_smem(); __syncwarp(); elect_arrive(bar_stm); } },
               k == 16, L_SPEC_B, NEXT_Q())
        L_EVEN:
          TURN(pb, pa, prev * (SLOT / 16) + 512, r.slot * (SLOT / 16), true,
               if (k == 9) { ROW_SUMS() l0 = 0.f; l1 = 0.f; n0 = 0.f; n1 = 0.f; slow = false; }, k == 9, L_SPEC_A, )
          goto L_ODD;
        L_SPEC_B:
          if (__any_sync(0xffffffffu, UNSAFE())) goto L_RARE;
        L_B2:
          l0 = u0; l1 = u1;
          if (k == 16) goto L_LAST;
          if (k == 8) {
#pragma unroll
            for (int i = 0; i < 8; i++) lds128(stash + i * 4096, qf[4 * i], qf[4 * i + 1], qf[4 * i + 2], qf[4 * i + 3]);
          }
          mbar_wait(bar_full + r.slot * 8, r.phase);
          goto L_EVEN;
        L_SPEC_A:
          if (k == 9) { pin(o); STAGE_O() }
          if (__any_sync(0xffffffffu, UNSAFE())) goto L_RARE;
        L_A2:
          l0 = u0; l1 = u1;
          mbar_wait(bar_full + r.slot * 8, r.phase);
          goto L_ODD;
        L_SLOW:
          pin(sx);
          redo = false;
#pragma unroll
          for (int i = 0; i < 8; i++) { sx[4 * i] += n0; sx[4 * i + 1] += n0; sx[4 * i + 2] += n1; sx[4 * i + 3] += n1; }
        L_EXP:
          EXPS(pa)
          if (__any_sync(0xffffffffu, UNSAFE() & !redo)) goto L_RARE;
          if (k & 1) goto L_A2;
#pragma unroll
          for (int i = 0; i < 16; i++) pb[i] = pa[i] ^ (ji >> 8);
          goto L_B2;
        L_LAST:
          {
            TOKEN_GET();
            wg_fence();
            ISSUE_PV(pb, dv_, true)
            TOKEN_PUT(true);
          }
          PROF_F(7);
          release_slot(bar_empty, rel, lane);
          ROW_SUMS()
          mbar_wait(bar_drm, 0);
          wg_wait<0>();
          pin(o);
          PROF_T(8);
          release_slot(bar_empty, prev, lane);
          STAGE_O()
          fence_async_smem();
          __syncwarp();
          elect_arrive(bar_stm);
          continue;
        L_RARE:
          {
            pin(o);
            float x0 = fmaxf(sx[0], sx[1]), x1 = fmaxf(sx[2], sx[3]);
#pragma unroll
            for (int i = 1; i < 8; i++) {
              x0 = fmaxf(x0, fmaxf(sx[4 * i], sx[4 * i + 1]));
              x1 = fmaxf(x1, fmaxf(sx[4 * i + 2], sx[4 * i + 3]));
            }
            x0 = fmaxf(x0, __shfl_xor_sync(0xffffffffu, x0, 1)); x1 = fmaxf(x1, __shfl_xor_sync(0xffffffffu, x1, 1));
            x0 = fmaxf(x0, __shfl_xor_sync(0xffffffffu, x0, 2)); x1 = fmaxf(x1, __shfl_xor_sync(0xffffffffu, x1, 2));
            if ((k & 7) != 1) {
              x0 = fmaxf(x0, 0.f); x1 = fmaxf(x1, 0.f);
              const float a0 = ex2(-x0), a1 = ex2(-x1);
              l0 *= a0; l1 *= a1;
#pragma unroll
              for (int i = 0; i < 16; i++) { o[4 * i] *= a0; o[4 * i + 1] *= a0; o[4 * i + 2] *= a1; o[4 * i + 3] *= a1; }
            }
            n0 -= x0; n1 -= x1;
            slow = true; redo = true;
#pragma unroll
            for (int i = 0; i < 8; i++) { sx[4 * i] -= x0; sx[4 * i + 1] -= x0; sx[4 * i + 2] -= x1; sx[4 * i + 3] -= x1; }
          }
          goto L_EXP;
        }
      }
    }
#pragma unroll 1
    for (; jn < NJOB; jn++) {
      const int ji = __shfl_sync(0xffffffffu, jn, 0);
      const uint32_t jq = job_get(job_addr, ji);
#define END_ARRIVE() asm volatile("barrier.cluster.arrive.relaxed.aligned;" ::: "memory")
      if ((JOB(jq).x & 3) == 0) { END_ARRIVE(); break; }
      {
        float c0[96], c1[64];
        PROF_T(1);
        const int ns = (JOB(jq).x >> 17) & 255;
        const bool fin = ((JOB(jq).x >> 25) & 3) == 0;
        const uint32_t wm = (JOB(jq).x >> 27) & 3;
        const uint32_t st0 = JSTART(jq);
        uint32_t mask = JOB(jq).z, slot = st0, prev;
#define OP_LOOP(WM, NSL, SSZ)                                                                                        \
  {                                                                                                                  \
    constexpr int KB = ((SSZ) - 8192) / 32;                                                                          \
    {                                                                                                                \
      mbar_wait(bar_ofull + slot * 8, (mask >> slot) & 1);                                                           \
      const uint64_t da = mkdesc(sb + slot * (SSZ) + wg * 1024, D_O);                                                \
      const uint64_t db = mkdesc(sb + slot * (SSZ) + 8192, D_W);                                                     \
      wg_fence();                                                                                                    \
      if ((WM) != 3) WgSS<192, 0, 1>::mma0(c0, da, db);              \
      WgSS<128, 0, 1>::mma0(c1, da, db + ((WM) == 0 ? 384 : 0));                                                     \
      if ((WM) < 2) WgSS<192, 0, 1>::mma(c0, da + 256, db + KB, 1);                                                 \
      if ((WM) != 1) WgSS<128, 0, 1>::mma(c1, da + 256, db + KB + ((WM) == 0 ? 384 : 0), 1);                         \
      wg_commit();                                                                                                   \
      mask ^= 1u << slot;                                                                                            \
      prev = slot;                                                                                                   \
      ONEXT(slot, st0, NSLOT * SLOT / (SSZ), NSL)                                                                    \
    }                                                                                                                \
    _Pragma("unroll 1") for (int st = 1; st < ns - ((WM) == 0 ? TL : 0); st++) {                                     \
      const uint32_t base = sb + slot * (SSZ);                                                                       \
      mbar_wait(bar_ofull + slot * 8, (mask >> slot) & 1);                                                           \
      const uint64_t da = mkdesc(base + wg * 1024, D_O);                                                             \
      const uint64_t db = mkdesc(base + 8192, D_W);                                                                  \
      wg_fence();                                                                                                    \
      _Pragma("unroll") for (int kk = 0; kk < 2; kk++) {                                                             \
        if ((WM) < 2) WgSS<192, 0, 1>::mma(c0, da + kk * 256, db + kk * KB, 1);                                     \
        if ((WM) != 1) WgSS<128, 0, 1>::mma(c1, da + kk * 256, db + kk * KB + ((WM) == 0 ? 384 : 0), 1);             \
      }                                                                                                              \
      wg_commit();                                                                                                   \
      wg_wait<1>();                                                                                                  \
      if (signaller && st <= ns - (NSL)) elect_arrive_cluster2(empty0 + OEMPTY + prev * 8, empty1 + OEMPTY + prev * 8);     \
      mask ^= 1u << slot;                                                                                            \
      prev = slot;                                                                                                   \
      ONEXT(slot, st0, NSLOT * SLOT / (SSZ), NSL)                                                                    \
      if ((st & 7) == 7) PROF_T(11);                                                                                 \
      if (st < 24) PROF_F(5);                                                                                        \
    }                                                                                                                \
  }
#define ST_BOX(dst, c, q0)                                                                                           \
  _Pragma("unroll") for (int i = 0; i < 4; i++)                                                                      \
    stsm4((dst) ^ (i * 32), pack_bf16(c[(q0) * 4 + 8 * i], c[(q0) * 4 + 8 * i + 1]), pack_bf16(c[(q0) * 4 + 8 * i + 2], c[(q0) * 4 + 8 * i + 3]), \
          pack_bf16(c[(q0) * 4 + 8 * i + 4], c[(q0) * 4 + 8 * i + 5]), pack_bf16(c[(q0) * 4 + 8 * i + 6], c[(q0) * 4 + 8 * i + 7]));
#define OUT_BOXES(c, b0, n)                                                                                          \
  {                                                                                                                  \
    _Pragma("unroll") for (int x = 0; x < (n); x++) { ST_BOX(sw + x * 2048, c, ((b0) + x) * 8) }                     \
    __syncwarp();                                                                                                    \
    uint4 v[4 * (n)];                                                                                                \
    _Pragma("unroll") for (int i = 0; i < 4 * (n); i++)                                                              \
      lds128((sr + i * 512) ^ ((i & 1) * 64), v[i].x, v[i].y, v[i].z, v[i].w);                                       \
    _Pragma("unroll") for (int i = 0; i < 4 * (n); i++) *(uint4*)(go + (i & 3) * (4 * D_ * 2) + (i >> 2) * 128) = v[i]; \
    __syncwarp();                                                                                                    \
    go += (n) * 128;                                                                                                 \
  }
        if (wm == 0) {
          constexpr int TL = ONS0 - 1;
          static_assert(ONS0 == 8, "");
          OP_LOOP(0, ONS0, 28672)
#pragma unroll 1
          for (int st = 0; st < TL; st++) {
            mbar_wait(bar_ofull + slot * 8, (mask >> slot) & 1);
            const uint64_t da = mkdesc(sb + slot * 28672 + wg * 1024, D_O), db = mkdesc(sb + slot * 28672 + 8192, D_W);
            wg_fence();
            WgSS<192, 0, 1>::mma(c0, da, db, 1);
            WgSS<192, 0, 1>::mma(c0, da + 256, db + 640, 1);
            wg_commit();
            wg_wait<1>();
            ONEXT(slot, st0, 5, 8)
          }
#define C1_MMA(a, b)                                                                                                 \
  wg_fence();                                                                                                        \
  _Pragma("unroll") for (int st = (a); st <= (b); st++) {                                                            \
    const uint32_t base = sb + ((prev + st) & 7) * 28672;                                                            \
    const uint64_t da = mkdesc(base + wg * 1024, D_O), db = mkdesc(base + 8192, D_W);                                \
    WgSS<128, 0, 1>::mma(c1, da, db + 384, 1);                                                                       \
    WgSS<128, 0, 1>::mma(c1, da + 256, db + 640 + 384, 1);                                                           \
  }                                                                                                                  \
  wg_commit();
          if (JOB(jq).x & J_LAST) END_ARRIVE();
          bar_sync(2, 256);
          C1_MMA(1, CA)
          const uint32_t jx = JOB(jq).x;
          const int lane = lane_id();
          const uint32_t strip = sb + prev * 28672 + warp * 2048;
          const uint32_t sw = strip + (lane & 15) * 128 + (((lane >> 4) ^ (lane & 7)) << 4);
          const uint32_t sr = strip + (lane >> 3) * 128 + (((lane ^ (lane >> 3)) & 7) << 4);
          uint8_t* go = (uint8_t*)out + (size_t)((((jx >> 4) & 31) * 2 + rank) * 128 + warp * 16 + (lane >> 3)) * (D_ * 2) +
                        ((JOB(jq).y >> 16) & 15) * 128 + (lane & 7) * 16;
          wg_wait<1>();
          pin(c0);
          PROF_T(8);
          OUT_BOXES(c0, 0, 1)
          C1_MMA(CA + 1, CB)
          OUT_BOXES(c0, 1, 1)
          C1_MMA(CB + 1, TL)
          OUT_BOXES(c0, 2, 1)
          wg_wait<0>();
          pin(c1);
          PROF_T(9);
          if (signaller && lane < 2 * TL && !(jx & J_LAST)) arrive_cluster_addr(((lane & 1) ? empty1 : empty0) + OEMPTY + ((prev + 1 + (lane >> 1)) & 7) * 8);
          OUT_BOXES(c1, 0, 1) OUT_BOXES(c1, 1, 1)
          if (jx & J_LAST) break;
          fence_async_smem();
          bar_sync(8 + wg, 128);
          if (signaller) elect_arrive_cluster2(empty0 + OEMPTY + prev * 8, empty1 + OEMPTY + prev * 8);
          continue;
        }
        constexpr int TL = 0;
        const uint32_t jx = JOB(jq).x;
        const int lane = lane_id();
        if (fin) {
          if (wm == 1) OP_LOOP(1, ONS1, 20480) else OP_LOOP(2, ONS2, 16384)
          wg_wait<0>();
          END_ARRIVE();
          PROF_T(8);
          const uint32_t nsl = op_nsl(wm), ssz = op_ssz(wm);
          const uint32_t sl = prev >= (uint32_t)wg ? prev - wg : nsl - 1;
          const uint32_t strip = sb + sl * ssz + (warp & 3) * (ssz / 4);
          const uint32_t sw = strip + (lane & 15) * 128 + (((lane >> 4) ^ (lane & 7)) << 4);
          const uint32_t sr = strip + (lane >> 3) * 128 + (((lane ^ (lane >> 3)) & 7) << 4);
          uint8_t* go = (uint8_t*)out + (size_t)((((jx >> 4) & 31) * 2 + rank) * 128 + warp * 16 + (lane >> 3)) * (D_ * 2) +
                        ((JOB(jq).y >> 16) & 15) * 128 + (lane & 7) * 16;
          bar_sync(2, 256);
          if (wm == 1) { OUT_BOXES(c0, 0, 2) OUT_BOXES(c0, 2, 1) } else OUT_BOXES(c1, 0, 2)
        } else {
          uint32_t real = 0;
#pragma unroll
          for (int i = 0; i < 64; i++) c1[i] = 0.f;
          prev = 0;
        L_OP:
          if (real) {
            OP_LOOP(3, ONS2, 16384)
            wg_wait<0>();
            END_ARRIVE();
          }
          PROF_T(8);
          const uint32_t jy = JOB(jq).y;
          const int pslot = jy & 255, gbase = (jy >> 8) & 255, idx = pslot - gbase;
          const uint32_t tag = (epoch_get(epoch_addr) ^ real ^ 1) & 1;
          uint4* dst = g_part + (size_t)(pslot * 2 + rank) * 2048 + warp * 32 + lane;
          float own[16];
#pragma unroll
          for (int i = 0; i < 16; i++) own[i] = 0.f;
#define PK(i) ((pack_bf16(c1[i], c1[(i) + 1]) & ~1u) | tag)
#pragma unroll
          for (int k = 0; k < 4; k++) {
            if (k != idx) {
#pragma unroll
              for (int i = 0; i < 2; i++)
                asm volatile("st.relaxed.gpu.global.v4.b32 [%0], {%1,%2,%3,%4};" ::"l"(dst + (2 * k + i) * 256), "r"(PK(16 * k + 8 * i)),
                             "r"(PK(16 * k + 8 * i + 2)), "r"(PK(16 * k + 8 * i + 4)), "r"(PK(16 * k + 8 * i + 6)) : "memory");
            } else {
#pragma unroll
              for (int i = 0; i < 16; i++) own[i] = c1[16 * k + i];
            }
          }
          PROF_T(9);
          uint32_t v[3][8];
#pragma unroll
          for (int i = 0; i < 24; i++) v[i >> 3][i & 7] = 0;
          uint32_t miss = real * 7;
#pragma unroll 1
          for (uint32_t it = 0;; it++) {
#pragma unroll
            for (int t = 0; t < 3; t++) {
              const uint4* src = g_part + (size_t)((gbase + ((idx + 1 + t) & 3)) * 2 + rank) * 2048 + idx * 512 + warp * 32 + lane;
#pragma unroll
              for (int i = 0; i < 2; i++)
                asm volatile("{\n.reg .pred p;\nsetp.ne.u32 p, %5, 0;\n@p ld.relaxed.gpu.global.v4.b32 {%0,%1,%2,%3}, [%4];\n}\n"
                             : "+r"(v[t][4 * i]), "+r"(v[t][4 * i + 1]), "+r"(v[t][4 * i + 2]), "+r"(v[t][4 * i + 3])
                             : "l"(src + i * 256), "r"(miss & (1 << t)) : "memory");
            }
            miss = 0;
#pragma unroll
            for (int t = 0; t < 3; t++) {
              uint32_t bad = 0;
#pragma unroll
              for (int i = 0; i < 8; i++) bad |= v[t][i] ^ tag;
              miss |= (bad & 1) << t;
            }
            miss = __reduce_or_sync(0xffffffffu, miss) * real;
            if (!miss) break;
            asm volatile("{\n.reg .pred p;\nsetp.gt.u32 p, %0, 4000000;\n@p trap;\n}\n" ::"r"(it));
            asm volatile("nanosleep.u32 %0;" ::"r"(miss & (miss - 1) ? XSLEEP2 : XSLEEP));
          }
          PROF_T(10);
#define LO(x) __uint_as_float(((x) << 16) & 0xfffe0000u)
#define HI(x) __uint_as_float((x) & 0xffff0000u)
#define SUM4(i) pack_bf16((own[2 * (i)] + LO(v[0][i])) + (LO(v[1][i]) + LO(v[2][i])), (own[2 * (i) + 1] + HI(v[0][i])) + (HI(v[1][i]) + HI(v[2][i])))
          const uint32_t strip = sb + prev * 16384 + warp * 256;
          const uint32_t sw = strip + (lane & 15) * 16 + (lane >> 4) * 2048;
#pragma unroll
          for (int i = 0; i < 2; i++)
            asm volatile("{\n.reg .pred p;\nsetp.ne.u32 p, %5, 0;\n@p stmatrix.sync.aligned.m8n8.x4.shared.b16 [%0], {%1,%2,%3,%4};\n}\n" ::"r"(sw + i * 4096),
                         "r"(SUM4(4 * i)), "r"(SUM4(4 * i + 1)), "r"(SUM4(4 * i + 2)), "r"(SUM4(4 * i + 3)), "r"(real) : "memory");
          __syncwarp();
          uint8_t* go = (uint8_t*)out + (size_t)((((jx >> 4) & 31) * 2 + rank) * 128 + warp * 16 + (lane >> 2)) * (D_ * 2) + ((jy >> 16) & 15) * 128 +
                        idx * 64 + (lane & 3) * 16;
#pragma unroll
          for (int i = 0; i < 2; i++) {
            uint4 y;
            lds128(strip + (lane & 3) * 2048 + ((lane >> 2) + i * 8) * 16, y.x, y.y, y.z, y.w);
            asm volatile("{\n.reg .pred p;\nsetp.ne.u32 p, %5, 0;\n@p st.global.v4.b32 [%0], {%1,%2,%3,%4};\n}\n" ::"l"(go + i * 8 * D_ * 2),
                         "r"(y.x), "r"(y.y), "r"(y.z), "r"(y.w), "r"(real) : "memory");
          }
          if (!real) {
            real = __shfl_sync(0xffffffffu, 1 + (ji >> 8), 0);
            goto L_OP;
          }
        }
        break;
      }
    }
    PROF_T(1);
    PROF_DUMP();
    if (wg == 0) TOKEN_GET();
    __syncwarp();
    asm volatile("barrier.cluster.wait.aligned;" ::: "memory");
  } else {
    asm volatile("setmaxnreg.dec.sync.aligned.u32 104;");
    {
      const uint32_t ju = __shfl_sync(0xffffffffu, (jx0 & J_PRE) ? ((jx0 & J_Q3) ? jz0 : jy0) : jx0, 0), jx = ju;
      const int b = ((ju >> 4) & 15) + rank * 16, hp = (ju >> 8) & 15;
      START_WAIT();
      if (warp == 8 && !(jx & J_DUMMY) && elect_one()) {
        QP_LOAD(sb, bar_full, 0)
#pragma unroll 1
        for (int s = 1; s < NSLOT; s++) {
          QP_LOAD(sb + s * SLOT, bar_full + s * 8, s)
        }
      }
      __syncwarp();
    }
    const int w = warp & 3;
    const uint32_t red = sb + OFF_RED;
#define SOFF()                                                                               \
  uint32_t soff0;                                                                            \
  {                                                                                          \
    const int lane = lane_id();                                                              \
    soff0 = (w * 16 + (lane & 15)) * 64 + ((((lane >> 4)) ^ ((lane >> 1) & 3)) << 4);        \
  }
#define XRED(x, OP)                                                                          \
  const int lane = lane_id();                                                                \
  const uint32_t rslot = ((lane & 3) * 8 + (lane >> 2)) * 4;                                 \
  const bool up16 = lane & 16, up8 = lane & 8, up4 = lane & 4;                               \
  _Pragma("unroll") for (int i = 0; i < 4; i++) {                                            \
    const float snd = up16 ? x[i] : x[i + 4], kp = up16 ? x[i + 4] : x[i];                   \
    x[i] = OP(kp, __shfl_xor_sync(0xffffffffu, snd, 16));                                    \
  }                                                                                          \
  _Pragma("unroll") for (int i = 0; i < 2; i++) {                                            \
    const float snd = up8 ? x[i] : x[i + 2], kp = up8 ? x[i + 2] : x[i];                     \
    x[i] = OP(kp, __shfl_xor_sync(0xffffffffu, snd, 8));                                     \
  }                                                                                          \
  {                                                                                          \
    const float snd = up4 ? x[0] : x[1], kp = up4 ? x[1] : x[0];                             \
    x[0] = OP(kp, __shfl_xor_sync(0xffffffffu, snd, 4));                                     \
  }
#define FADD_(a, b) ((a) + (b))
#define W2_GET() bar_sync(7, 256)
#define W2_PUT() bar_arrive(ORDER ? 6 : 5, 256)
#define W2_PUT_IF(c) asm volatile("{\n.reg .pred p;\nsetp.ne.u32 p, %0, 0;\n@p bar.arrive %1, 256;\n}\n" ::"r"(c), "n"(ORDER ? 6 : 5) : "memory")
#define APPLY_N()                                                                                             \
  if (slow) {                                                                                                 \
    uint32_t y[8];                                                                                            \
    const uint32_t aa = sb + OFF_ALPHA + 512 + w * 128 + (lane_id() & 3) * 32;                                \
    lds128(aa, y[0], y[1], y[2], y[3]); lds128(aa + 16, y[4], y[5], y[6], y[7]);                              \
    _Pragma("unroll") for (int i = 0; i < 8; i++) {                                                           \
      const int e = (i >> 1) * 4 + (i & 1);                                                                   \
      const float nn = __uint_as_float(y[i]);                                                                 \
      a0[e] += nn; a0[e + 2] += nn; a1[e] += nn; a1[e + 2] += nn;                                             \
    }                                                                                                         \
  }
    bar_arrive(5, 256);
    int jn = 0;
#pragma unroll 1
    for (; jn < NJOB; jn++) {
      const int ji = __shfl_sync(0xffffffffu, jn, 0);
      const uint32_t jq = job_get(job_addr, ji);
      if ((JOB(jq).x & 3) != 1) break;
      Ring r = JRING(jq);
      {
        float a0[16], a1[16], a2[16], a3[16];
        PROF_T(1);
        if (signaller && elect_one()) mbar_expect_tx(bar_q, 8192);
        uint32_t jf = JOB(jq).x & (J_PRE | J_ATO | J_QO | J_Q3), xm = XST;
        if (jf & J_ATO) {
          mbar_wait(bar_full + r.slot * 8, r.phase);
          release_slot(bar_empty, r.slot, lane);
          r.next();
          mbar_wait(bar_q, ji & 1);
        } else for (;;) {
          float q[64];
          uint32_t prev = r.slot;
          {
            const uint32_t base = sb + r.slot * SLOT;
            mbar_wait(bar_full + r.slot * 8, r.phase);
            const uint64_t da = mkdesc(base + 8192, D_A64);
            const uint64_t db = mkdesc(base + A_TILE + rank * 4096, D_W);
            wg_fence();
            WgSS<128, 0, 1>::mma0(q, da, db);
            WgSS<128, 0, 1>::mma(q, da + 2, db + 512, 1);
            wg_commit();
            r.next();
          }
#pragma unroll 1
          for (int st = (JOB(jq).x & J_DUMMY) ? 17 : 1; st < 20; st++) {
            const bool xs = (xm >> st) & 1;
            const uint32_t sl = xs ? NSLOT + ((st ^ (st >> 3) ^ 1) & 1) : r.slot;
            const uint32_t base = sb + sl * SLOT;
            mbar_wait(bar_full + sl * 8, xs ? st >> 3 : r.phase);
            if (st == 12) bulk_wait_read();
            const uint64_t da = mkdesc(base + 8192, D_A64);
            const uint64_t db = mkdesc(base + A_TILE + rank * 4096, D_W);
            wg_fence();
            WgSS<128, 0, 1>::mma(q, da, db, 1);
            WgSS<128, 0, 1>::mma(q, da + 2, db + 512, 1);
            wg_commit();
            wg_wait<1>();
            release_slot(bar_empty, prev, lane);
            prev = sl;
            if (!xs) r.next();
          }
          wg_wait<0>();
          release_slot(bar_empty, prev, lane);
          const int lane = lane_id();
          const bool own = (uint32_t)(w >> 1) == rank;
          PROF_T(2);
          if (!jf) mbar_wait(xm ? bar_drl : bar_empty + NSLOT * 8, xm ? (ji & 1) ^ 1 : (JOB(jq).x & J_Q3) != 0);
          const uint32_t qs = jf ? sb + w * SLOT + 28672 : sb + (own ? OFF_QL : OFF_PT + 8192) + (w & 1) * 2048, qh = jf ? 2048 : 4096;
          const uint32_t dst = qs + (lane & 15) * 128 + (((lane >> 4) ^ (lane & 7)) << 4);
#pragma unroll
          for (int i = 0; i < 8; i++)
            stsm4((dst + (i >> 2) * qh) ^ ((i & 3) * 32), pack_bf16(q[8 * i] * SCALE_LOG2, q[8 * i + 1] * SCALE_LOG2),
                  pack_bf16(q[8 * i + 2] * SCALE_LOG2, q[8 * i + 3] * SCALE_LOG2), pack_bf16(q[8 * i + 4] * SCALE_LOG2, q[8 * i + 5] * SCALE_LOG2),
                  pack_bf16(q[8 * i + 6] * SCALE_LOG2, q[8 * i + 7] * SCALE_LOG2));
          fence_async_smem();
          __syncwarp();
          if (jf) {
            if (lane < 2)
              bulk_store(g_q + ((JOB(jq).y >> 16) * 2 + (w >> 1) + (jf == J_QO ? 2 : 0) + ((JOB(jq).x & ~jf & J_Q3) ? 2 : 0)) * Q_BYTES + (own ? 65536 : 65536 + 8192) + lane * 4096 + (w & 1) * 2048,
                         qs + lane * 2048, 2048);
            bulk_commit();
            if (jf == J_QO) break;
            jf &= (jf & J_Q3) ? ~J_Q3 : J_QO; xm = 0;
            continue;
          }
          if (!own && lane < 2)
            asm volatile("cp.async.bulk.shared::cluster.shared::cta.mbarrier::complete_tx::bytes [%0], [%1], 2048, [%2];"
                         ::"r"(mapa(sb + OFF_QL + 8192 + lane * 4096 + (w & 1) * 2048, rank ^ 1)),
                           "r"(qs + lane * 4096), "r"(mapa(bar_q, rank ^ 1)) : "memory");
          break;
        }
        if (jf == J_QO) {
          bulk_wait_read();
          bar_sync(1, 128);
          if (signaller) elect_arrive_cluster2(empty0 + XFREE, empty1 + XFREE);
          bulk_wait_all();
          bar_sync(1, 128);
          if (signaller && elect_one()) asm volatile("red." FLAGSEM ".gpu.global.add.u32 [%0], 1;" ::"l"(&g_oflag[B_ * H_ + pair + rank * QFLAG]) : "memory");
          break;
        }
#pragma unroll
        for (int i = 0; i < 16; i++) { a2[i] = 0.f; a3[i] = 0.f; }
        float l[8];
        int slow = 0;
#pragma unroll
        for (int i = 0; i < 8; i++) l[i] = 0.f;
#define STAGE_OT(hh)                                                                                          \
  {                                                                                                           \
    const int lane = lane_id();                                                                               \
    float l[8];                                                                                               \
    _Pragma("unroll") for (int ww = 0; ww < 4; ww++)                                                          \
      asm volatile("ld.shared.f32 %0, [%1];" : "=f"(l[ww]) : "r"(red + 512 + ww * 128 + lane * 4) : "memory"); \
    const float rs = rcp_approx((l[0] + l[1]) + (l[2] + l[3]));                                               \
    _Pragma("unroll") for (int i = 0; i < 8; i++) l[i] = __shfl_sync(0xffffffffu, rs, (lane & 3) * 8 + i);    \
    const uint32_t stg = sb + OFF_QL + (hh) * 8192 + w * 1024 + lane * 16;                                    \
    stsm4t(stg, pack_bf16(a2[0] * l[0], a2[1] * l[1]), pack_bf16(a2[4] * l[2], a2[5] * l[3]),                 \
           pack_bf16(a2[8] * l[4], a2[9] * l[5]), pack_bf16(a2[12] * l[6], a2[13] * l[7]));                   \
    stsm4t(stg + 512, pack_bf16(a2[2] * l[0], a2[3] * l[1]), pack_bf16(a2[6] * l[2], a2[7] * l[3]),           \
           pack_bf16(a2[10] * l[4], a2[11] * l[5]), pack_bf16(a2[14] * l[6], a2[15] * l[7]));                 \
    stsm4t(stg + 4096, pack_bf16(a3[0] * l[0], a3[1] * l[1]), pack_bf16(a3[4] * l[2], a3[5] * l[3]),          \
           pack_bf16(a3[8] * l[4], a3[9] * l[5]), pack_bf16(a3[12] * l[6], a3[13] * l[7]));                   \
    stsm4t(stg + 4608, pack_bf16(a3[2] * l[0], a3[3] * l[1]), pack_bf16(a3[6] * l[2], a3[7] * l[3]),          \
           pack_bf16(a3[10] * l[4], a3[11] * l[5]), pack_bf16(a3[14] * l[6], a3[15] * l[7]));                 \
    fence_async_smem();                                                                                       \
    __syncwarp();                                                                                             \
    elect_arrive(bar_stl + (hh) * 72);                                                                                  \
  }
#define EXPS_T(a, h)                                                                                          \
  {                                                                                                           \
    uint32_t pt[8];                                                                                           \
    _Pragma("unroll") for (int i = 0; i < 4; i++) {                                                           \
      pt[2 * i] = pack_bf16(ex2(a[4 * i]), ex2(a[4 * i + 1]));                                                \
      pt[2 * i + 1] = pack_bf16(ex2(a[4 * i + 2]), ex2(a[4 * i + 3]));                                        \
      c[i] = (h) ? hadd2(c[i], hadd2(pt[2 * i], pt[2 * i + 1])) : hadd2(pt[2 * i], pt[2 * i + 1]);            \
    }                                                                                                         \
    stsm4(po + (h) * 4096, pt[0], pt[1], pt[2], pt[3]);                                                       \
    stsm4((po ^ 32) + (h) * 4096, pt[4], pt[5], pt[6], pt[7]);                                                \
  }
        {
          int step = 0;
          uint32_t vslot = 0, da, dv, dp, po;
          uint32_t c[4];
          { SOFF() po = sb + OFF_PT + soff0; }
          c[0] = 0; c[1] = 0; c[2] = 0; c[3] = 0;
#define ADD_C()                                                                                               \
  _Pragma("unroll") for (int i = 0; i < 4; i++) { l[2 * i] += __uint_as_float(c[i] << 16); l[2 * i + 1] += __uint_as_float(c[i] & 0xffff0000u); }
          da = (uint32_t)D_K + sb4 + r.slot * (SLOT / 16);
          mbar_wait(bar_full + r.slot * 8, r.phase);
          bar_sync(1, 128);
          goto W_ST;
        W_TOP:
          PROF_F(7);
          ADD_C()
          if ((step & 3) < 2) {
            if (step == 1) {
              mbar_wait(bar_q + 8, ji & 1);
              mbar_wait(bar_drl, (ji & 1) ^ 1);
            }
            if (step == 4) {
              bulk_wait_all();
              XRED(l, FADD_)
              asm volatile("st.shared.f32 [%0], %1;" ::"r"(red + 512 + w * 128 + rslot), "f"(l[0]) : "memory");
#pragma unroll
              for (int i = 0; i < 8; i++) l[i] = 0.f;
              slow = 0;
            }
            if (step == 5) STAGE_OT(0)
          }
          wg_wait<0>();
          pin(a0); pin(a1);
          elect_arrive_cluster2_if(empty0 + r.slot * 8, empty1 + r.slot * 8, signaller);
          r.next();
          PROF_F(3);
          APPLY_N()
          EXPS_T(a0, 0)
          PROF_F(4);
          if (step == 0) {
            mbar_wait(bar_q, ji & 1);
            if (signaller && elect_one()) arrive_cluster_addr(mapa(bar_q + 8, rank ^ 1));
            goto W_B;
          }
          W2_GET();
        W_PV:
          if (WPOS2 == 0) W2_PUT();
          wg_fence();
#pragma unroll
          for (int k = 0; k < 8; k++) {
            WgSS<32, 1, 1>::mma(a2, DESC(D_V, dv + k * 128), DESC(D_N64, dp + k * 64), (step & 3) != 1 || k != 0);
            WgSS<32, 1, 1>::mma(a3, DESC(D_V, dv + 1024 + k * 128), DESC(D_N64, dp + k * 64), (step & 3) != 1 || k != 0);
            if (WPOS2 == k + 1 && k < 7) W2_PUT();
          }
          wg_commit();
          if (WPOS2 == 8) W2_PUT();
          PROF_F(6);
          if (step == 8) goto W_END;
        W_B:
          pin(a1);
          EXPS_T(a1, 1)
          if ((umax2(umax2(umax2(c[0], c[1]), umax2(c[2], c[3])), HI2) != HI2) |
              ((umin2(umin2(umin2(c[0], c[1]), umin2(c[2], c[3])), LO2) != LO2) & ((step & 3) == 0)))
            asm volatile("st.shared.u32 [%0], %1;" ::"r"(sb + OFF_BAR + 240), "r"(1) : "memory");
          wg_wait<0>();
          pin(a2); pin(a3);
          elect_arrive_cluster2_if(empty0 + vslot * 8, empty1 + vslot * 8, signaller && step > 0);
          vslot = r.slot;
          dv = (uint32_t)D_V + sb4 + vslot * (SLOT / 16);
          dp = (uint32_t)D_N64 + sb4 + OFF_PT / 16 + (step & 1) * 512;
          mbar_wait(bar_full + r.slot * 8, r.phase);
          r.next();
          da = (uint32_t)D_K + sb4 + r.slot * (SLOT / 16);
          if (step < 7) mbar_wait(bar_full + r.slot * 8, r.phase);
          fence_async_smem();
          PROF_F(9);
          W2_GET();
          {
            uint32_t upd;
            asm volatile("ld.shared.u32 %0, [%1];" : "=r"(upd) : "r"(sb + OFF_BAR + 240) : "memory");
            if (__builtin_expect(__any_sync(0xffffffffu, upd != 0), 0)) goto W_RARE;
          }
        W_OK:
          step++;
          po ^= 8192;
          if (step == 8) goto W_PV;
        W_ST:
          {
            const uint32_t dq = (uint32_t)D_K + sb4 + OFF_QL / 16 + (step >> 2) * 512;
            if (WPOS == 0) W2_PUT_IF(step);
            wg_fence();
            WgSS<32, 0, 0>::mma0(a0, DESC(D_K, da), DESC(D_K, dq));
            WgSS<32, 0, 0>::mma0(a1, DESC(D_K, da + 512), DESC(D_K, dq));
            if (WPOS == 1) W2_PUT_IF(step);
#pragma unroll
            for (int k = 1; k < 8; k++) {
              WgSS<32, 0, 0>::mma(a0, DESC(D_K, da + (k >> 2) * 1024 + (k & 3) * 2), DESC(D_K, dq + (k >> 2) * 256 + (k & 3) * 2), 1);
              WgSS<32, 0, 0>::mma(a1, DESC(D_K, da + 512 + (k >> 2) * 1024 + (k & 3) * 2), DESC(D_K, dq + (k >> 2) * 256 + (k & 3) * 2), 1);
              if (WPOS == k + 1 && k < 7) W2_PUT_IF(step);
            }
            wg_commit();
            if (WPOS == 8) W2_PUT_IF(step);
          }
          goto W_TOP;
        W_RARE:
          {
            const int j = step & 3;
            float x[8];
#pragma unroll
            for (int i = 0; i < 4; i++) {
              x[2 * i] = fmaxf(fmaxf(a0[4 * i], a0[4 * i + 2]), fmaxf(a1[4 * i], a1[4 * i + 2]));
              x[2 * i + 1] = fmaxf(fmaxf(a0[4 * i + 1], a0[4 * i + 3]), fmaxf(a1[4 * i + 1], a1[4 * i + 3]));
            }
            XRED(x, fmaxf)
            asm volatile("st.shared.f32 [%0], %1;" ::"r"(red + w * 128 + rslot), "f"(x[0]) : "memory");
            bar_sync(1, 128);
            asm volatile("st.shared.u32 [%0], %1;" ::"r"(sb + OFF_BAR + 240), "r"(0) : "memory");
            float m = j != 0 ? 0.f : -INFINITY, nn = 0.f;
#pragma unroll
            for (int ww = 0; ww < 4; ww++) {
              float y;
              asm volatile("ld.shared.f32 %0, [%1];" : "=f"(y) : "r"(red + ww * 128 + lane * 4) : "memory");
              m = fmaxf(m, y);
            }
            const uint32_t aa = sb + OFF_ALPHA + w * 128;
            if (slow) asm volatile("ld.shared.f32 %0, [%1];" : "=f"(nn) : "r"(aa + 512 + lane * 4) : "memory");
            asm volatile("st.shared.f32 [%0], %1;" ::"r"(aa + 512 + lane * 4), "f"(nn - m) : "memory");
            asm volatile("st.shared.f32 [%0], %1;" ::"r"(aa + lane * 4), "f"(m) : "memory");
            __syncwarp();
#pragma unroll
            for (int h = 0; h < 2; h++) {
              uint32_t y[4];
              lds128(aa + (lane & 3) * 32 + h * 16, y[0], y[1], y[2], y[3]);
#pragma unroll
              for (int i = 4 * h; i < 4 * h + 4; i++) {
                const int e = (i >> 1) * 4 + (i & 1);
                const float xx = __uint_as_float(y[i & 3]), al = j != 0 ? ex2(-xx) : 1.f;
                l[i] *= al; a2[e] *= al; a2[e + 2] *= al; a3[e] *= al; a3[e + 2] *= al;
                a0[e] -= xx; a0[e + 2] -= xx; a1[e] -= xx; a1[e + 2] -= xx;
              }
            }
            slow = 1;
            pin(a0); pin(a1);
            EXPS_T(a0, 0)
            EXPS_T(a1, 1)
            fence_async_smem();
            bar_sync(1, 128);
          }
          goto W_OK;
        W_END:
          {
            ADD_C()
            XRED(l, FADD_)
            asm volatile("st.shared.f32 [%0], %1;" ::"r"(red + 512 + w * 128 + rslot), "f"(l[0]) : "memory");
          }
          bar_sync(1, 128);
          wg_wait<0>();
          pin(a2); pin(a3);
          release_slot(bar_empty, vslot, lane);
          PROF_T(8);
          STAGE_OT(1)
        }
      }
    }
    PROF_T(1);
    PROF_DUMP();
    __syncwarp();
    cluster_sync();
  }
}

typedef CUresult (*EncodeFn)(CUtensorMap*, CUtensorMapDataType, cuuint32_t, void*, const cuuint64_t*, const cuuint64_t*,
                             const cuuint32_t*, const cuuint32_t*, CUtensorMapInterleave, CUtensorMapSwizzle,
                             CUtensorMapL2promotion, CUtensorMapFloatOOBfill);

void make_map(EncodeFn enc, CUtensorMap* tm, const void* ptr, int rank, const cuuint64_t* dims, const cuuint64_t* strides,
              const cuuint32_t* box, CUtensorMapSwizzle swz, CUtensorMapL2promotion promo,
              CUtensorMapDataType dt = CU_TENSOR_MAP_DATA_TYPE_BFLOAT16) {
  cuuint32_t es[3] = {1, 1, 1};
  enc(tm, dt, rank, const_cast<void*>(ptr), dims, strides, box, es,
      CU_TENSOR_MAP_INTERLEAVE_NONE, swz, promo, CU_TENSOR_MAP_FLOAT_OOB_FILL_NONE);
}

}

extern "C" void kernel_launch(void* const* d_in, const int* in_sizes, int n_in, void* d_out, int out_size) {
  (void)in_sizes; (void)n_in; (void)out_size;
  static EncodeFn enc = nullptr;
  if (!enc) {
    void* fn = nullptr;
    cudaDriverEntryPointQueryResult qr;
    cudaGetDriverEntryPoint("cuTensorMapEncodeTiled", &fn, cudaEnableDefault, &qr);
    enc = (EncodeFn)fn;
    cudaFuncSetAttribute(fused_kernel, cudaFuncAttributeMaxDynamicSharedMemorySize, SMEM_BYTES);
  }
  const void* x = d_in[0]; const void* kc = d_in[1]; const void* vc = d_in[2]; const void* wq = d_in[3]; const void* wo = d_in[4];
  Params prm;
  {
    cuuint64_t dims[2] = {D_, (cuuint64_t)B_ * SQ}; cuuint64_t str[1] = {D_ * 2}; cuuint32_t box[2] = {32, 128};
    make_map(enc, &prm.tm_x, x, 2, dims, str, box, CU_TENSOR_MAP_SWIZZLE_64B, CU_TENSOR_MAP_L2_PROMOTION_L2_128B);
    box[1] = 32;
    make_map(enc, &prm.tm_xl, x, 2, dims, str, box, CU_TENSOR_MAP_SWIZZLE_64B, CU_TENSOR_MAP_L2_PROMOTION_L2_128B);
  }
  {
    cuuint64_t dims[3] = {64, D_, 64}; cuuint64_t str[2] = {8192, 128}; cuuint32_t box[3] = {64, 16, 4};
    make_map(enc, &prm.tm_wq, wq, 3, dims, str, box, CU_TENSOR_MAP_SWIZZLE_128B, CU_TENSOR_MAP_L2_PROMOTION_L2_256B);
  }
  {
    cuuint64_t dims[3] = {64, 4096, 10}; cuuint64_t str[2] = {1280, 128}; cuuint32_t box[3] = {64, 16, 5};
    make_map(enc, &prm.tm_wo, wo, 3, dims, str, box, CU_TENSOR_MAP_SWIZZLE_128B, CU_TENSOR_MAP_L2_PROMOTION_L2_128B);
    box[2] = 3;
    make_map(enc, &prm.tm_wo3, wo, 3, dims, str, box, CU_TENSOR_MAP_SWIZZLE_128B, CU_TENSOR_MAP_L2_PROMOTION_L2_128B);
    box[2] = 2;
    make_map(enc, &prm.tm_wo2, wo, 3, dims, str, box, CU_TENSOR_MAP_SWIZZLE_128B, CU_TENSOR_MAP_L2_PROMOTION_L2_128B);
  }
  {
    cuuint64_t dims[3] = {64, (cuuint64_t)B_ * H_ * SK, 2}; cuuint64_t str[2] = {256, 128}; cuuint32_t box[3] = {64, 128, 2};
    make_map(enc, &prm.tm_k, kc, 3, dims, str, box, CU_TENSOR_MAP_SWIZZLE_128B, CU_TENSOR_MAP_L2_PROMOTION_L2_256B);
    make_map(enc, &prm.tm_v, vc, 3, dims, str, box, CU_TENSOR_MAP_SWIZZLE_128B, CU_TENSOR_MAP_L2_PROMOTION_L2_256B);
  }
  {
    void* po = nullptr;
    cudaGetSymbolAddress(&po, g_o);
    cuuint64_t dims[2] = {O_PLANE / 8, 512}; cuuint64_t str[1] = {O_PLANE}; cuuint32_t box[2] = {256, 4};
    make_map(enc, &prm.tm_o, po, 2, dims, str, box, CU_TENSOR_MAP_SWIZZLE_NONE, CU_TENSOR_MAP_L2_PROMOTION_L2_128B,
             CU_TENSOR_MAP_DATA_TYPE_UINT64);
  }
  {
    cuuint64_t dims[2] = {D_, (cuuint64_t)B_ * SQ}; cuuint64_t str[1] = {D_ * 2}; cuuint32_t box[2] = {64, 64};
    make_map(enc, &prm.tm_out, d_out, 2, dims, str, box, CU_TENSOR_MAP_SWIZZLE_128B, CU_TENSOR_MAP_L2_PROMOTION_NONE);
  }
  fused_kernel<<<2 * NPAIR, 512, SMEM_BYTES>>>((const uint8_t*)x, (const uint8_t*)wq, (const __nv_bfloat16*)kc, (const __nv_bfloat16*)vc,
                                                (__nv_bfloat16*)d_out, prm);
}
```
